```python
import torch

def _softmax(x, axis=-1):
    return torch.softmax(x, dim=axis)

def _gelu(x):
    return torch.nn.functional.gelu(x, approximate='tanh')

def _silu(x):
    return torch.nn.functional.silu(x)

def _sigmoid(x):
    return torch.sigmoid(x)

def _layernorm(x, axis=-1, eps=1e-05):
    m = x.mean(dim=axis, keepdim=True)
    v = x.var(dim=axis, keepdim=True, unbiased=False)
    return (x - m) / torch.sqrt(v + eps)

def _scatter_add(tgt, idx, src, axis=0):
    return tgt.clone().index_add_(axis, idx, src)

def _segment_sum(src, seg, n):
    out = torch.zeros((n,) + src.shape[1:], dtype=src.dtype)
    return out.index_add_(0, seg, src)

def _pad(x, pw):
    flat = tuple((v for pair in reversed(pw) for v in pair))
    return torch.nn.functional.pad(x, flat)
kernel_name = 'gather_scatter__molecular_angular_painn__graph'

def setup_inputs():

    _w = lambda a: (lambda t: t.to(torch.bfloat16) if t.is_floating_point() else t)(torch.as_tensor(a))
    N, deg, D = (10000, 64, 64)
    n_rbf = max(16, 4)
    E = N * deg
    cutoff = 5.0
    freqs = (torch.arange(1, n_rbf + 1) * torch.pi / cutoff).to(float)
    return {'sv': _w((lambda *s: torch.randn(*s, dtype=torch.bfloat16) * 0.4)(N, 4, D) * 0.3), 'pos': _w((lambda *s: torch.randn(*s, dtype=torch.bfloat16) * 1.6)(N, 3) * 1.2), 'src': _w((lambda lo, hi, *s: torch.randint(lo, hi, s))(0, N, E).to(torch.int64)), 'dst': _w((lambda lo, hi, *s: torch.randint(lo, hi, s))(0, N, E).to(torch.int64)), 'freqs': _w(freqs), 'w_phi1': _w((lambda *s: torch.randn(*s, dtype=torch.bfloat16) * 3.2)(D, D) / D ** 0.5), 'w_phi2': _w((lambda *s: torch.randn(*s, dtype=torch.bfloat16) * 1.6)(D, 3 * D) / D ** 0.5), 'w_rbf': _w((lambda *s: torch.randn(*s, dtype=torch.bfloat16) * 1.6)(n_rbf, 3 * D) / n_rbf ** 0.5)}

def reference(sv, pos, src, dst, freqs, w_phi1, w_phi2, w_rbf):
    N, _, D = sv.shape
    E = src.shape[0]
    PI, cutoff = (3.141592653589793, 5.0)
    s, v = (sv[:, 0, :].clone(), sv[:, 1:, :].clone())
    r_vec = pos[src] - pos[dst]
    d = torch.sqrt((r_vec * r_vec).sum(-1) + 1e-08)
    r_hat = r_vec / d[:, None]
    rbf = torch.sin(d[:, None] * freqs[None, :]) / d[:, None]
    fcut = 0.5 * (torch.cos(PI * d / cutoff) + 1.0)
    fcut = torch.where(d < cutoff, fcut, 0.0 * d)
    Wf = rbf @ w_rbf * fcut[:, None]
    phi = (_silu(s @ w_phi1) @ w_phi2)[src]
    m = phi * Wf
    m_s, m_vv, m_vr = (m[:, :D].clone(), m[:, D:2 * D].clone(), m[:, 2 * D:].clone())
    ds = _segment_sum(m_s, dst, N)
    dv_e = m_vv[:, None, :] * v[src] + m_vr[:, None, :] * r_hat[:, :, None]
    dv = _segment_sum(dv_e.reshape(E, 3 * D), dst, N).reshape(N, 3, D)
    return sv + torch.concatenate([ds[:, None, :], dv], axis=1)
```

```cpp
#include <cuda_runtime.h>
#include <cuda_bf16.h>
#include <stdint.h>

namespace {

constexpr int NN = 10000;
constexpr int CAP = 128;
constexpr int MAXE = 640000;
constexpr int RT_LO = 0x38C0;
constexpr int RT_HI = 0x40A0;
constexpr int RT_N = RT_HI - RT_LO;

__device__ uint4 g_table[NN * 32];
__device__ uint2 g_rec[NN * CAP];
__device__ int g_cnt[NN];
__device__ int g_head[NN];
__device__ uint4 g_ovf[MAXE];
__device__ int g_ovf_cnt;
__device__ int g_sched;
__device__ uint4 g_rtab[RT_N * 2];

__device__ __forceinline__ float bf16r(float x) { return __bfloat162float(__float2bfloat16_rn(x)); }
__device__ __forceinline__ float bf_lo(uint32_t u) { return __uint_as_float(u << 16); }
__device__ __forceinline__ float bf_hi(uint32_t u) { return __uint_as_float(u & 0xffff0000u); }
__device__ __forceinline__ uint32_t pack_bf(float lo, float hi) {
    uint32_t r;
    asm("cvt.rn.bf16x2.f32 %0, %1, %2;" : "=r"(r) : "f"(hi), "f"(lo));
    return r;
}
__device__ __forceinline__ uint32_t hmul2_bf(uint32_t a, uint32_t b) {
    uint32_t r;
    asm("mul.rn.bf16x2 %0, %1, %2;" : "=r"(r) : "r"(a), "r"(b));
    return r;
}
__device__ __forceinline__ uint32_t smem_u32(const void* p) { return (uint32_t)__cvta_generic_to_shared(p); }
__device__ __forceinline__ void mbar_init(uint32_t bar, int cnt) {
    asm volatile("mbarrier.init.shared.b64 [%0], %1;" ::"r"(bar), "r"(cnt) : "memory");
}
__device__ __forceinline__ void mbar_arrive(uint32_t bar) {
    asm volatile("mbarrier.arrive.shared.b64 _, [%0];" ::"r"(bar) : "memory");
}
__device__ __forceinline__ void mbar_expect_tx(uint32_t bar, uint32_t bytes) {
    asm volatile("mbarrier.arrive.expect_tx.shared.b64 _, [%0], %1;" ::"r"(bar), "r"(bytes) : "memory");
}
__device__ __forceinline__ void mbar_wait(uint32_t bar, uint32_t parity) {
    uint32_t ok;
    int it = 0;
    do {
        asm volatile(
            "{.reg .pred p; mbarrier.try_wait.parity.shared.b64 p, [%1], %2; selp.u32 %0, 1, 0, p;}"
            : "=r"(ok) : "r"(bar), "r"(parity) : "memory");
        if (++it > (1 << 24)) __trap();
    } while (!ok);
}
__device__ __forceinline__ void bulk_g2s(uint32_t dst, const void* src, uint32_t bytes, uint32_t bar) {
    asm volatile("cp.async.bulk.shared::cluster.global.mbarrier::complete_tx::bytes [%0], [%1], %2, [%3];"
                 ::"r"(dst), "l"(src), "r"(bytes), "r"(bar) : "memory");
}
__device__ __forceinline__ void ldsm_x4(uint32_t* r, uint32_t a) {
    asm volatile("ldmatrix.sync.aligned.m8n8.x4.shared.b16 {%0,%1,%2,%3}, [%4];"
                 : "=r"(r[0]), "=r"(r[1]), "=r"(r[2]), "=r"(r[3]) : "r"(a));
}
__device__ __forceinline__ void ldsm_x4_t(uint32_t* r, uint32_t a) {
    asm volatile("ldmatrix.sync.aligned.m8n8.x4.trans.shared.b16 {%0,%1,%2,%3}, [%4];"
                 : "=r"(r[0]), "=r"(r[1]), "=r"(r[2]), "=r"(r[3]) : "r"(a));
}
__device__ __forceinline__ void mma16816(float* d, const uint32_t* a, uint32_t b0, uint32_t b1) {
    asm volatile("mma.sync.aligned.m16n8k16.row.col.f32.bf16.bf16.f32 {%0,%1,%2,%3},{%4,%5,%6,%7},{%8,%9},{%0,%1,%2,%3};"
                 : "+f"(d[0]), "+f"(d[1]), "+f"(d[2]), "+f"(d[3])
                 : "r"(a[0]), "r"(a[1]), "r"(a[2]), "r"(a[3]), "r"(b0), "r"(b1));
}

__device__ __forceinline__ float edge_dist(float rx, float ry, float rz) {
    float q = bf16r(bf16r(rx * rx) + bf16r(ry * ry) + bf16r(rz * rz));
    q = bf16r(q + 1e-08f);
    return bf16r(sqrtf(q));
}

constexpr int PRE_BLOCKS = 125;
constexpr int PRE_EW = 20;
constexpr int PRE_NW = 5;
constexpr int PRE_THREADS = (PRE_EW + PRE_NW + 1) * 32;
constexpr int SVROW = 528;
constexpr int WROW = 144;
constexpr int PRE_SM_POS = 0;
constexpr int PRE_SM_SV = 60160;
constexpr int PRE_SM_W = PRE_SM_SV + PRE_NW * 16 * SVROW;
constexpr int PRE_SM_BAR = PRE_SM_W + 2 * 64 * WROW;
constexpr int PRE_SMEM = PRE_SM_BAR + 64;

__global__ void __launch_bounds__(PRE_THREADS, 1)
pre_kernel(const __nv_bfloat16* __restrict__ sv, const __nv_bfloat16* __restrict__ pos,
           const int* __restrict__ src, const int* __restrict__ dst,
           const __nv_bfloat16* __restrict__ freqs, const __nv_bfloat16* __restrict__ w1,
           const __nv_bfloat16* __restrict__ w2, int E) {
    extern __shared__ __align__(128) unsigned char sm[];
    const int tid = threadIdx.x, warp = tid >> 5, lane = tid & 31;
    const uint32_t sb = smem_u32(sm);
    const uint32_t bar_pos = sb + PRE_SM_BAR, bar_sv = bar_pos + 8;
    if (tid == 0) {
        mbar_init(bar_pos, 1);
        for (int i = 0; i < PRE_NW; i++) mbar_init(bar_sv + 8 * i, 1);
        asm volatile("fence.proxy.async.shared::cta;" ::: "memory");
        mbar_expect_tx(bar_pos, NN * 6);
        bulk_g2s(sb + PRE_SM_POS, pos, NN * 6, bar_pos);
    }
    __syncthreads();

    if (warp < PRE_EW) {
        const int ngrp = E >> 2;
        const int g0 = blockIdx.x * (PRE_EW * 64) + tid;
        int4 s4[2], d4[2];
#pragma unroll
        for (int r = 0; r < 2; r++) {
            int g = g0 + r * PRE_EW * 32;
            if (g < ngrp) {
                s4[r] = __ldcs(reinterpret_cast<const int4*>(src) + g);
                d4[r] = __ldcs(reinterpret_cast<const int4*>(dst) + g);
            } else {
                s4[r] = make_int4(-1, -1, -1, -1);
                d4[r] = make_int4(0, 0, 0, 0);
            }
        }
        mbar_wait(bar_pos, 0);
        const uint32_t* pw = reinterpret_cast<const uint32_t*>(sm + PRE_SM_POS);
        int es[8] = {s4[0].x, s4[0].y, s4[0].z, s4[0].w, s4[1].x, s4[1].y, s4[1].z, s4[1].w};
        int ed[8] = {d4[0].x, d4[0].y, d4[0].z, d4[0].w, d4[1].x, d4[1].y, d4[1].z, d4[1].w};
        uint2 rec[8];
        int slot[8];
#pragma unroll
        for (int i = 0; i < 8; i++) {
            bool valid = es[i] >= 0;
            int a = valid ? es[i] : 0, b = ed[i];
            int wa = (3 * a) >> 1, wb = (3 * b) >> 1;
            uint32_t a0 = pw[wa], a1 = pw[wa + 1], b0 = pw[wb], b1 = pw[wb + 1];
            uint32_t axy = (a & 1) ? __byte_perm(a0, a1, 0x5432) : a0;
            uint32_t az = (a & 1) ? (a1 & 0xffff0000u) : (a1 << 16);
            uint32_t bxy = (b & 1) ? __byte_perm(b0, b1, 0x5432) : b0;
            uint32_t bz = (b & 1) ? (b1 & 0xffff0000u) : (b1 << 16);
            float rx = bf16r(bf_lo(axy) - bf_lo(bxy));
            float ry = bf16r(bf_hi(axy) - bf_hi(bxy));
            float rz = bf16r(__uint_as_float(az) - __uint_as_float(bz));
            float d = edge_dist(rx, ry, rz);
            float arg = bf16r(bf16r(3.14159265358979f * d) / 5.0f);
            float fc = bf16r(bf16r(__cosf(arg)) + 1.0f);
            bool act = valid && (d < 5.0f) && (fc != 0.0f);
            rec[i].x = (uint32_t)a | (__float_as_uint(rx) & 0xffff0000u);
            rec[i].y = (__float_as_uint(ry) >> 16) | (__float_as_uint(rz) & 0xffff0000u);
            slot[i] = act ? atomicAdd(&g_cnt[b], 1) : -1;
        }
#pragma unroll
        for (int i = 0; i < 8; i++) {
            if (slot[i] >= 0) {
                if (slot[i] < CAP) {
                    g_rec[ed[i] * CAP + slot[i]] = rec[i];
                } else {
                    int o = atomicAdd(&g_ovf_cnt, 1);
                    int nx = atomicExch(&g_head[ed[i]], o + 1);
                    g_ovf[o] = make_uint4(rec[i].x, rec[i].y, (uint32_t)nx, 0u);
                }
            }
        }
    } else if (warp < PRE_EW + PRE_NW) {
        const int nw = warp - PRE_EW;
        const int node0 = (blockIdx.x * PRE_NW + nw) * 16;
        const uint32_t svb = sb + PRE_SM_SV + nw * 16 * SVROW;
        const uint32_t bar = bar_sv + 8 * nw;
        if (lane == 0) mbar_expect_tx(bar, 16 * 512);
        __syncwarp();
        if (lane < 16) bulk_g2s(svb + lane * SVROW, sv + (size_t)(node0 + lane) * 256, 512, bar);
        for (int i = nw * 32 + lane; i < 1024; i += PRE_NW * 32) {
            int m = i >> 9, r = (i >> 3) & 63, c = i & 7;
            uint4 v = m == 0 ? reinterpret_cast<const uint4*>(w1)[r * 8 + c]
                             : reinterpret_cast<const uint4*>(w2)[r * 24 + 8 + c];
            *reinterpret_cast<uint4*>(sm + PRE_SM_W + (m * 64 + r) * WROW + c * 16) = v;
        }
        asm volatile("bar.sync 1, %0;" ::"n"(PRE_NW * 32) : "memory");
        mbar_wait(bar, 0);
        const int g = lane >> 2, q = lane & 3;
        uint32_t a[4][4];
#pragma unroll
        for (int kk = 0; kk < 4; kk++)
            ldsm_x4(a[kk], svb + (lane & 15) * SVROW + kk * 32 + (lane >> 4) * 16);
        float acc[8][4];
        uint32_t hb[8][2];
#pragma unroll
        for (int m = 0; m < 2; m++) {
#pragma unroll
            for (int nt = 0; nt < 8; nt++) acc[nt][0] = acc[nt][1] = acc[nt][2] = acc[nt][3] = 0.f;
            const uint32_t wb = sb + PRE_SM_W + m * 64 * WROW;
#pragma unroll
            for (int kk = 0; kk < 4; kk++) {
#pragma unroll
                for (int np = 0; np < 4; np++) {
                    uint32_t b[4];
                    ldsm_x4_t(b, wb + (kk * 16 + (lane & 15)) * WROW + np * 32 + (lane >> 4) * 16);
                    mma16816(acc[2 * np], a[kk], b[0], b[1]);
                    mma16816(acc[2 * np + 1], a[kk], b[2], b[3]);
                }
            }
            if (m == 0) {
#pragma unroll
                for (int nt = 0; nt < 8; nt++) {
                    float t[4];
#pragma unroll
                    for (int i = 0; i < 4; i++) {
                        float x = bf16r(acc[nt][i]);
                        t[i] = x / (1.0f + __expf(-x));
                    }
                    hb[nt][0] = pack_bf(t[0], t[1]);
                    hb[nt][1] = pack_bf(t[2], t[3]);
                }
#pragma unroll
                for (int kk = 0; kk < 4; kk++) {
                    a[kk][0] = hb[2 * kk][0];
                    a[kk][1] = hb[2 * kk][1];
                    a[kk][2] = hb[2 * kk + 1][0];
                    a[kk][3] = hb[2 * kk + 1][1];
                }
            }
        }
#pragma unroll
        for (int r = 0; r < 2; r++) {
            const unsigned char* vrow = sm + PRE_SM_SV + (nw * 16 + g + 8 * r) * SVROW + q * 4;
            uint4* orow = g_table + (size_t)(node0 + g + 8 * r) * 32 + q;
#pragma unroll
            for (int nt = 0; nt < 8; nt++) {
                uint32_t ph = pack_bf(acc[nt][2 * r], acc[nt][2 * r + 1]);
                uint4 o;
                o.x = hmul2_bf(ph, *reinterpret_cast<const uint32_t*>(vrow + 128 + nt * 16));
                o.y = hmul2_bf(ph, *reinterpret_cast<const uint32_t*>(vrow + 256 + nt * 16));
                o.z = hmul2_bf(ph, *reinterpret_cast<const uint32_t*>(vrow + 384 + nt * 16));
                o.w = hb[nt][r];
                orow[nt * 4] = o;
            }
        }
    } else {
        if (blockIdx.x == 0 && lane == 0) g_sched = 0;
        for (int i = blockIdx.x * 32 + lane; i < RT_N * 2; i += PRE_BLOCKS * 32) {
            float d = __uint_as_float((uint32_t)(RT_LO + (i >> 1)) << 16);
            float arg = bf16r(bf16r(3.14159265358979f * d) / 5.0f);
            float fc = bf16r(0.5f * bf16r(bf16r(cosf(arg)) + 1.0f));
            float r[8];
#pragma unroll
            for (int k = 0; k < 8; k++) {
                float f = __bfloat162float(freqs[(i & 1) * 8 + k]);
                r[k] = bf16r(bf16r(sinf(bf16r(d * f))) / d) * fc;
            }
            g_rtab[i] = make_uint4(pack_bf(r[0], r[1]), pack_bf(r[2], r[3]), pack_bf(r[4], r[5]), pack_bf(r[6], r[7]));
        }
    }
}

constexpr int NCW = 3;
constexpr int NB = 4;
constexpr int NS = 8;
constexpr int MAIN_THREADS = (NCW + 1) * 128;
constexpr uint32_t META_FIRST = 1u << 16, META_LAST = 1u << 17, META_END = 1u << 18;
constexpr uint32_t NOROW = 0xffffffffu;

constexpr int SM_W2 = 0;
constexpr int SM_CST = SM_W2 + 16384;
constexpr int SM_T = SM_CST + 6 * 128 * 16;
constexpr int SM_TILE = SM_T + NCW * 8192;
constexpr int SM_IDX = SM_TILE + NCW * NS * 2048;
constexpr int SM_BAR = SM_IDX + NCW * NS * 80;
constexpr int MAIN_SMEM = SM_BAR + NCW * (2 * NS + 1) * 8;

__device__ __forceinline__ uint64_t mkdesc(uint32_t addr, uint32_t lbo, uint32_t sbo) {
    return (uint64_t)((addr & 0x3FFFF) >> 4) | ((uint64_t)(lbo >> 4) << 16) | ((uint64_t)(sbo >> 4) << 32);
}
#define WG_FENCE() asm volatile("wgmma.fence.sync.aligned;" ::: "memory")
#define WG_COMMIT() asm volatile("wgmma.commit_group.sync.aligned;" ::: "memory")
#define WG_WAIT0() asm volatile("wgmma.wait_group.sync.aligned 0;" ::: "memory")

#define F8(d, o) "+f"(d[o + 0]), "+f"(d[o + 1]), "+f"(d[o + 2]), "+f"(d[o + 3]), "+f"(d[o + 4]), "+f"(d[o + 5]), "+f"(d[o + 6]), "+f"(d[o + 7])

__device__ __forceinline__ void wg_rs_n16(float* d, const uint32_t* a, uint64_t b, uint32_t acc) {
    asm volatile(
        "{.reg .pred p; setp.ne.u32 p, %13, 0;\n"
        "wgmma.mma_async.sync.aligned.m64n16k16.f32.bf16.bf16 {%0,%1,%2,%3,%4,%5,%6,%7},{%8,%9,%10,%11},%12,p,1,1,1;}"
        : F8(d, 0) : "r"(a[0]), "r"(a[1]), "r"(a[2]), "r"(a[3]), "l"(b), "r"(acc));
}
__device__ __forceinline__ void wg_rs_n64(float* d, const uint32_t* a, uint64_t b, uint32_t acc) {
    asm volatile(
        "{.reg .pred p; setp.ne.u32 p, %37, 0;\n"
        "wgmma.mma_async.sync.aligned.m64n64k16.f32.bf16.bf16 "
        "{%0,%1,%2,%3,%4,%5,%6,%7,%8,%9,%10,%11,%12,%13,%14,%15,%16,%17,%18,%19,%20,%21,%22,%23,%24,%25,%26,%27,%28,%29,%30,%31},"
        "{%32,%33,%34,%35},%36,p,1,1,1;}"
        : F8(d, 0), F8(d, 8), F8(d, 16), F8(d, 24)
        : "r"(a[0]), "r"(a[1]), "r"(a[2]), "r"(a[3]), "l"(b), "r"(acc));
}
template <int ACC>
__device__ __forceinline__ void wg_ss_n16(float* d, uint64_t a, uint64_t b) {
    asm volatile(
        "wgmma.mma_async.sync.aligned.m64n16k16.f32.bf16.bf16 {%0,%1,%2,%3,%4,%5,%6,%7},%8,%9,%10,1,1,0,1;"
        : F8(d, 0) : "l"(a), "l"(b), "n"(ACC));
}
template <int ACC>
__device__ __forceinline__ void wg_ss_n48(float* d, uint64_t a, uint64_t b) {
    asm volatile(
        "wgmma.mma_async.sync.aligned.m64n48k16.f32.bf16.bf16 "
        "{%0,%1,%2,%3,%4,%5,%6,%7,%8,%9,%10,%11,%12,%13,%14,%15,%16,%17,%18,%19,%20,%21,%22,%23},%24,%25,%26,1,1,0,1;"
        : F8(d, 0), F8(d, 8), F8(d, 16) : "l"(a), "l"(b), "n"(ACC));
}
__device__ __forceinline__ void ld_row(uint4& v, const unsigned char* base, uint32_t row) {
    asm volatile(
        "{.reg .pred p; .reg .b64 a; setp.ne.u32 p, %5, 0xffffffff; mad.wide.u32 a, %5, 512, %4;\n"
        "@p ld.global.L1::no_allocate.v4.u32 {%0,%1,%2,%3}, [a];}"
        : "+r"(v.x), "+r"(v.y), "+r"(v.z), "+r"(v.w) : "l"(base), "r"(row));
}
__device__ __forceinline__ uint4 lds128(uint32_t a) {
    uint4 v;
    asm volatile("ld.shared.v4.u32 {%0,%1,%2,%3}, [%4];" : "=r"(v.x), "=r"(v.y), "=r"(v.z), "=r"(v.w) : "r"(a) : "memory");
    return v;
}
__device__ __forceinline__ uint32_t lds32(uint32_t a) {
    uint32_t v;
    asm volatile("ld.shared.u32 %0, [%1];" : "=r"(v) : "r"(a) : "memory");
    return v;
}
__device__ __forceinline__ void sts128(uint32_t a, uint32_t x, uint32_t y, uint32_t z, uint32_t w) {
    asm volatile("st.shared.v4.u32 [%0], {%1,%2,%3,%4};" ::"r"(a), "r"(x), "r"(y), "r"(z), "r"(w) : "memory");
}
__device__ __forceinline__ void sts32(uint32_t a, uint32_t x) {
    asm volatile("st.shared.u32 [%0], %1;" ::"r"(a), "r"(x) : "memory");
}

__global__ void __launch_bounds__(MAIN_THREADS, 1)
main_kernel(const __nv_bfloat16* __restrict__ sv, const __nv_bfloat16* __restrict__ w2,
            const __nv_bfloat16* __restrict__ wr, __nv_bfloat16* __restrict__ out) {
    extern __shared__ __align__(128) unsigned char sm[];
    const int tid = threadIdx.x, lane = tid & 31, wg = tid >> 7;
    const uint32_t sb = smem_u32(sm);

    for (int i = tid; i < 2 * 4096; i += MAIN_THREADS) {
        int p = i >> 12, m = (i >> 6) & 63, k = i & 63;
        int c = 2 * ((m >> 4) * 8 + (m & 7)) + ((m >> 3) & 1);
        int j = 2 * ((k >> 4) * 8 + (k & 7)) + ((k >> 3) & 1);
        *reinterpret_cast<__nv_bfloat16*>(sm + SM_W2 + p * 8192 + (m >> 3) * 1024 + (k >> 3) * 128 + (m & 7) * 16 + (k & 7) * 2) =
            w2[j * 192 + p * 128 + c];
    }
    for (int i = tid; i < 6 * 128 * 4; i += MAIN_THREADS) {
        int e = i & 3, t = (i >> 2) & 127, ph = i >> 9;
        int part = ph >> 1, half = ph & 1;
        int r = e >> 1, k = 8 * half + 2 * (t & 3) + (e & 1);
        int c = 2 * ((t >> 5) * 8 + ((t & 31) >> 2)) + r;
        reinterpret_cast<float*>(sm + SM_CST)[i] = __bfloat162float(wr[k * 192 + part * 64 + c]);
    }
    if (tid == 0) {
        for (int w = 0; w < NCW; w++) {
            for (int s = 0; s < NS; s++) {
                mbar_init(sb + SM_BAR + (w * (2 * NS + 1) + s) * 8, 1);
                mbar_init(sb + SM_BAR + (w * (2 * NS + 1) + NS + s) * 8, 4);
            }
            mbar_init(sb + SM_BAR + (w * (2 * NS + 1) + 2 * NS) * 8, 4);
        }
    }
    asm volatile("fence.proxy.async.shared::cta;" ::: "memory");
    __syncthreads();

    if (wg == NCW) {
        asm volatile("setmaxnreg.dec.sync.aligned.u32 56;");
        const int cw = (tid >> 5) & 3;
        if (cw < NCW) {
            if (blockIdx.x == 0 && cw == 0 && lane == 0) g_ovf_cnt = 0;
            const uint32_t bfull = sb + SM_BAR + cw * (2 * NS + 1) * 8, bempty = bfull + NS * 8;
            const uint32_t tile0 = sb + SM_TILE + cw * NS * 2048, idx0 = sb + SM_IDX + cw * NS * 80;
            uint32_t pos = 0;
            const int s16 = lane & 15, hi = lane >> 4;
            const uint32_t tile_lane = (s16 >> 3) * 128 + (s16 & 7) * 16;
            const uint32_t idx_lane = (4 * ((s16 & 7) >> 1) + (s16 & 1) + 2 * (s16 >> 3)) * 4;

            auto emit = [&](uint2 rec, bool valid, bool two, uint32_t meta0, uint32_t meta1) {
                float rx = bf_hi(rec.x), ry = bf_lo(rec.y), rz = bf_hi(rec.y);
                float d = edge_dist(rx, ry, rz);
                int di = (int)(__float_as_uint(d) >> 16) - RT_LO;
                di = min(max(di, 0), RT_N - 1);
                uint4 r0 = make_uint4(0, 0, 0, 0), r1 = r0;
                if (valid) {
                    r0 = __ldg(&g_rtab[2 * di]);
                    r1 = __ldg(&g_rtab[2 * di + 1]);
                }
                uint32_t hx = pack_bf(rx / d, rx / d), hy = pack_bf(ry / d, ry / d), hz = pack_bf(rz / d, rz / d);
                if (!valid) hx = hy = hz = 0;
                uint32_t st0 = pos % NS, st1 = (pos + 1) % NS;
                mbar_wait(bempty + st0 * 8, ((pos / NS) & 1) ^ 1);
                if (two) mbar_wait(bempty + st1 * 8, (((pos + 1) / NS) & 1) ^ 1);
                uint32_t st = hi ? st1 : st0;
                if (two || !hi) {
                    uint32_t t = tile0 + st * 2048 + tile_lane;
                    sts128(t, r0.x, r0.y, r0.z, r0.w);
                    sts128(t + 256, r1.x, r1.y, r1.z, r1.w);
                    sts128(t + 512, hmul2_bf(r0.x, hx), hmul2_bf(r0.y, hx), hmul2_bf(r0.z, hx), hmul2_bf(r0.w, hx));
                    sts128(t + 768, hmul2_bf(r1.x, hx), hmul2_bf(r1.y, hx), hmul2_bf(r1.z, hx), hmul2_bf(r1.w, hx));
                    sts128(t + 1024, hmul2_bf(r0.x, hy), hmul2_bf(r0.y, hy), hmul2_bf(r0.z, hy), hmul2_bf(r0.w, hy));
                    sts128(t + 1280, hmul2_bf(r1.x, hy), hmul2_bf(r1.y, hy), hmul2_bf(r1.z, hy), hmul2_bf(r1.w, hy));
                    sts128(t + 1536, hmul2_bf(r0.x, hz), hmul2_bf(r0.y, hz), hmul2_bf(r0.z, hz), hmul2_bf(r0.w, hz));
                    sts128(t + 1792, hmul2_bf(r1.x, hz), hmul2_bf(r1.y, hz), hmul2_bf(r1.z, hz), hmul2_bf(r1.w, hz));
                    sts32(idx0 + st * 80 + idx_lane, valid ? (rec.x & 0xffffu) : NOROW);
                    if (s16 == 0) sts32(idx0 + st * 80 + 64, hi ? meta1 : meta0);
                }
                asm volatile("fence.proxy.async.shared::cta;" ::: "memory");
                __syncwarp();
                if (lane == 0) mbar_arrive(bfull + st0 * 8);
                if (two && lane == 16) mbar_arrive(bfull + st1 * 8);
                pos += two ? 2 : 1;
            };

            auto claim = [&]() { return lane == 0 ? atomicAdd(&g_sched, 1) : 0; };
            int n0 = __shfl_sync(~0u, claim(), 0);
            int n1 = __shfl_sync(~0u, claim(), 0);
            int n2 = __shfl_sync(~0u, claim(), 0);
            int c0 = n0 < NN ? g_cnt[n0] : 0, c1 = n1 < NN ? g_cnt[n1] : 0;
            uint2 ra[3], rb[3];
#pragma unroll
            for (int i = 0; i < 3; i++) {
                ra[i] = make_uint2(0, 0);
                if (i * 32 + lane < c0) ra[i] = g_rec[n0 * CAP + i * 32 + lane];
            }
            while (n0 < NN) {
                int n3r = claim();
                int c2 = n2 < NN ? g_cnt[n2] : 0;
#pragma unroll
                for (int i = 0; i < 3; i++) {
                    rb[i] = make_uint2(0, 0);
                    if (i * 32 + lane < c1) rb[i] = g_rec[n1 * CAP + i * 32 + lane];
                }
                if (lane == 0) g_cnt[n0] = 0;
                int ovf = 0;
                if (c0 > CAP) {
                    ovf = g_head[n0];
                    __syncwarp();
                    if (lane == 0) g_head[n0] = 0;
                }
                for (int base = 0; base == 0 || base < c0; base += 32) {
                    uint2 rec;
                    if (base == 0) rec = ra[0];
                    else if (base == 32) rec = ra[1];
                    else if (base == 64) rec = ra[2];
                    else if (base < CAP) {
                        rec = make_uint2(0, 0);
                        if (base + lane < c0) rec = g_rec[n0 * CAP + base + lane];
                    } else {
                        rec = make_uint2(0, 0);
                        for (int i = 0; i < 32 && ovf != 0; i++) {
                            uint4 o = g_ovf[ovf - 1];
                            if (i == lane) rec = make_uint2(o.x, o.y);
                            ovf = (int)o.z;
                        }
                    }
                    bool two = base + 16 < c0;
                    uint32_t m0 = (uint32_t)n0 | (base == 0 ? META_FIRST : 0u) | (two ? 0u : META_LAST);
                    uint32_t m1 = (uint32_t)n0 | (base + 32 >= c0 ? META_LAST : 0u);
                    emit(rec, base + lane < c0, two, m0, m1);
                }
                n0 = n1; c0 = c1;
                n1 = n2; c1 = c2;
                n2 = __shfl_sync(~0u, n3r, 0);
#pragma unroll
                for (int i = 0; i < 3; i++) ra[i] = rb[i];
            }
            for (int i = 0; i < NB; i += 2) emit(make_uint2(0, 0), false, true, META_END, META_END);
        }
    } else {
        asm volatile("setmaxnreg.inc.sync.aligned.u32 152;");
        const int t128 = tid & 127, w = t128 >> 5, q = lane & 3;
        const uint32_t bfull = sb + SM_BAR + wg * (2 * NS + 1) * 8, bempty = bfull + NS * 8, btfree = bfull + 2 * NS * 8;
        const uint32_t idx0 = sb + SM_IDX + wg * NS * 80;
        const uint64_t tile_desc = mkdesc(sb + SM_TILE + wg * NS * 2048, 128, 256);
        const uint32_t tsm = sb + SM_T + wg * 8192;
        const unsigned char* tb = reinterpret_cast<const unsigned char*>(g_table) + (t128 >> 2) * 16;
        const int ocol = q * 32 + (t128 >> 2);

        uint4 buf[NB][4];
        uint32_t meta[NB];
        float T[32], U[24];
#pragma unroll
        for (int i = 0; i < 32; i++) T[i] = 0.f;
#pragma unroll
        for (int i = 0; i < 24; i++) U[i] = 0.f;
        uint32_t fpos = 0;
        uint32_t tphase = 1;

        auto fetch = [&](uint4* b, uint32_t& m) {
            uint32_t st = fpos % NS;
            mbar_wait(bfull + st * 8, (fpos / NS) & 1);
            uint4 rows = lds128(idx0 + st * 80 + q * 16);
            m = lds32(idx0 + st * 80 + 64);
            ld_row(b[0], tb, rows.x);
            ld_row(b[1], tb, rows.y);
            ld_row(b[2], tb, rows.z);
            ld_row(b[3], tb, rows.w);
            fpos++;
        };
#pragma unroll
        for (int j = 0; j < NB; j++) {
#pragma unroll
            for (int i = 0; i < 4; i++) buf[j][i] = make_uint4(0, 0, 0, 0);
            fetch(buf[j], meta[j]);
        }
        bool pending = false;
        while (true) {
#pragma unroll
            for (int j = 0; j < NB; j++) {
                const uint32_t m = meta[j];
                if (m & META_END) goto done;
                const uint32_t st = (fpos - NB) % NS;
                if (pending) {
                    WG_WAIT0();
                    if (lane == 0) mbar_arrive(bempty + ((st + NS - 1) % NS) * 8);
                }
                uint32_t A[4][4];
                {
                    const uint4* b = buf[j];
                    A[0][0] = __byte_perm(b[0].x, b[1].x, 0x5410); A[0][1] = __byte_perm(b[0].x, b[1].x, 0x7632);
                    A[0][2] = __byte_perm(b[2].x, b[3].x, 0x5410); A[0][3] = __byte_perm(b[2].x, b[3].x, 0x7632);
                    A[1][0] = __byte_perm(b[0].y, b[1].y, 0x5410); A[1][1] = __byte_perm(b[0].y, b[1].y, 0x7632);
                    A[1][2] = __byte_perm(b[2].y, b[3].y, 0x5410); A[1][3] = __byte_perm(b[2].y, b[3].y, 0x7632);
                    A[2][0] = __byte_perm(b[0].z, b[1].z, 0x5410); A[2][1] = __byte_perm(b[0].z, b[1].z, 0x7632);
                    A[2][2] = __byte_perm(b[2].z, b[3].z, 0x5410); A[2][3] = __byte_perm(b[2].z, b[3].z, 0x7632);
                    A[3][0] = __byte_perm(b[0].w, b[1].w, 0x5410); A[3][1] = __byte_perm(b[0].w, b[1].w, 0x7632);
                    A[3][2] = __byte_perm(b[2].w, b[3].w, 0x5410); A[3][3] = __byte_perm(b[2].w, b[3].w, 0x7632);
                }
                const uint64_t bd = tile_desc + st * 128;
                const uint32_t acc = (m & META_FIRST) ? 0u : 1u;
                WG_FENCE();
                wg_rs_n64(T, A[3], bd, acc);
                wg_rs_n16(U, A[0], bd, acc);
                wg_rs_n16(U + 8, A[1], bd, acc);
                wg_rs_n16(U + 16, A[2], bd, acc);
                WG_COMMIT();
                pending = true;
                fetch(buf[j], meta[j]);
                if (m & META_LAST) {
                    const int node = m & 0xffff;
                    const uint32_t res = __ldg(reinterpret_cast<const uint32_t*>(sv) + node * 128 + ocol);
                    WG_WAIT0();
                    if (lane == 0) mbar_arrive(bempty + st * 8);
                    pending = false;
                    mbar_wait(btfree, tphase);
                    tphase ^= 1;
#pragma unroll
                    for (int i = 0; i < 4; i++) {
                        asm volatile("stmatrix.sync.aligned.m8n8.x4.shared.b16 [%0], {%1,%2,%3,%4};"
                                     ::"r"(tsm + w * 2048 + i * 512 + lane * 16),
                                     "r"(pack_bf(T[8 * i], T[8 * i + 1])), "r"(pack_bf(T[8 * i + 2], T[8 * i + 3])),
                                     "r"(pack_bf(T[8 * i + 4], T[8 * i + 5])), "r"(pack_bf(T[8 * i + 6], T[8 * i + 7]))
                                     : "memory");
                    }
                    asm volatile("fence.proxy.async.shared::cta;" ::: "memory");
                    asm volatile("bar.sync %0, 128;" ::"r"(wg + 1) : "memory");
                    const uint64_t td = mkdesc(tsm, 128, 256);
                    const uint64_t as = mkdesc(sb + SM_W2, 128, 1024), av = mkdesc(sb + SM_W2 + 8192, 128, 1024);
                    WG_FENCE();
                    wg_ss_n48<0>(T + 8, av, td + 32);
                    wg_ss_n16<0>(T, as, td);
#pragma unroll
                    for (int kk = 1; kk < 4; kk++) {
                        wg_ss_n48<1>(T + 8, av + kk * 16, td + kk * 128 + 32);
                        wg_ss_n16<1>(T, as + kk * 16, td + kk * 128);
                    }
                    WG_COMMIT();
                    float p[4][2];
                    {
                        const uint4 c0 = lds128(sb + SM_CST + (2 * 128 + t128) * 16);
                        const uint4 c1 = lds128(sb + SM_CST + (3 * 128 + t128) * 16);
#pragma unroll
                        for (int x = 0; x < 3; x++) {
                            const float* u = U + 8 * x;
                            p[x + 1][0] = u[0] * __uint_as_float(c0.x) + u[1] * __uint_as_float(c0.y) +
                                          u[4] * __uint_as_float(c1.x) + u[5] * __uint_as_float(c1.y);
                            p[x + 1][1] = u[2] * __uint_as_float(c0.z) + u[3] * __uint_as_float(c0.w) +
                                          u[6] * __uint_as_float(c1.z) + u[7] * __uint_as_float(c1.w);
                        }
                    }
                    const uint4 s0 = lds128(sb + SM_CST + (0 * 128 + t128) * 16);
                    const uint4 s1 = lds128(sb + SM_CST + (1 * 128 + t128) * 16);
                    const uint4 v0 = lds128(sb + SM_CST + (4 * 128 + t128) * 16);
                    const uint4 v1 = lds128(sb + SM_CST + (5 * 128 + t128) * 16);
                    WG_WAIT0();
                    if (lane == 0) mbar_arrive(btfree);
                    p[0][0] = T[0] * __uint_as_float(s0.x) + T[1] * __uint_as_float(s0.y) +
                              T[4] * __uint_as_float(s1.x) + T[5] * __uint_as_float(s1.y);
                    p[0][1] = T[2] * __uint_as_float(s0.z) + T[3] * __uint_as_float(s0.w) +
                              T[6] * __uint_as_float(s1.z) + T[7] * __uint_as_float(s1.w);
#pragma unroll
                    for (int x = 0; x < 3; x++) {
                        const float* y = T + 8 + 8 * x;
                        p[x + 1][0] += y[0] * __uint_as_float(v0.x) + y[1] * __uint_as_float(v0.y) +
                                       y[4] * __uint_as_float(v1.x) + y[5] * __uint_as_float(v1.y);
                        p[x + 1][1] += y[2] * __uint_as_float(v0.z) + y[3] * __uint_as_float(v0.w) +
                                       y[6] * __uint_as_float(v1.z) + y[7] * __uint_as_float(v1.w);
                    }
                    const bool q2 = q & 2, q1 = q & 1;
                    float k0[2], k1[2];
#pragma unroll
                    for (int r = 0; r < 2; r++) {
                        float sa = q2 ? p[0][r] : p[2][r], sbv = q2 ? p[1][r] : p[3][r];
                        k0[r] = (q2 ? p[2][r] : p[0][r]) + __shfl_xor_sync(~0u, sa, 2);
                        k1[r] = (q2 ? p[3][r] : p[1][r]) + __shfl_xor_sync(~0u, sbv, 2);
                    }
                    float o[2];
#pragma unroll
                    for (int r = 0; r < 2; r++) {
                        float sa = q1 ? k0[r] : k1[r];
                        o[r] = (q1 ? k1[r] : k0[r]) + __shfl_xor_sync(~0u, sa, 1);
                    }
                    reinterpret_cast<uint32_t*>(out)[node * 128 + ocol] = pack_bf(bf_lo(res) + o[0], bf_hi(res) + o[1]);
                }
            }
        }
    done:;
    }
}

}

extern "C" void kernel_launch(void* const* d_in, const int* in_sizes, int n_in, void* d_out, int out_size) {
    const __nv_bfloat16* sv = (const __nv_bfloat16*)d_in[0];
    const __nv_bfloat16* pos = (const __nv_bfloat16*)d_in[1];
    const int* src = (const int*)d_in[2];
    const int* dst = (const int*)d_in[3];
    const __nv_bfloat16* freqs = (const __nv_bfloat16*)d_in[4];
    const __nv_bfloat16* w1 = (const __nv_bfloat16*)d_in[5];
    const __nv_bfloat16* w2 = (const __nv_bfloat16*)d_in[6];
    const __nv_bfloat16* wr = (const __nv_bfloat16*)d_in[7];
    static int sms = 0;
    if (!sms) {
        cudaFuncSetAttribute(pre_kernel, cudaFuncAttributeMaxDynamicSharedMemorySize, PRE_SMEM);
        cudaFuncSetAttribute(main_kernel, cudaFuncAttributeMaxDynamicSharedMemorySize, MAIN_SMEM);
        int dev = 0;
        cudaGetDevice(&dev);
        cudaDeviceGetAttribute(&sms, cudaDevAttrMultiProcessorCount, dev);
    }
    pre_kernel<<<PRE_BLOCKS, PRE_THREADS, PRE_SMEM>>>(sv, pos, src, dst, freqs, w1, w2, in_sizes[2]);
    main_kernel<<<sms, MAIN_THREADS, MAIN_SMEM>>>(sv, w2, wr, (__nv_bfloat16*)d_out);
}
```

```cpp
#include <cuda_runtime.h>
#include <cuda_bf16.h>
#include <stdint.h>

namespace {

constexpr int NN = 10000;
constexpr int NE = 640000;
constexpr int G = 132;
constexpr int RT_LO = 0x38C0;
constexpr int RT_HI = 0x40A0;
constexpr int RT_N = RT_HI - RT_LO;
constexpr float D_ACTIVE = 4.90625f;

constexpr int THREADS = 512;
constexpr int CT = 384;
constexpr int ET = 352;
constexpr int EV = 3;
constexpr int EPT = EV * 4 + 2;
constexpr int E_VEC = G * ET * EV * 4;
constexpr int E_TAIL = ((NE - E_VEC) / 2 + G - 1) / G;
static_assert(E_TAIL <= ET, "tail");
constexpr int CB = 80;
constexpr uint32_t TAGMAX = 2047;
constexpr int NPG = (NN + G - 1) / G;
constexpr int NTILE = NN / 16;

constexpr size_t WIN = 1u << 24;
constexpr size_t RT_OFF = 1u << 22;
__device__ uint4 g_arena[(2 * WIN + NN * 256) / 16];
__device__ __forceinline__ unsigned char* arena_base() {
    return reinterpret_cast<unsigned char*>((reinterpret_cast<uint64_t>(g_arena) + WIN - 1) & ~(uint64_t)(WIN - 1));
}
__device__ uint4 g_xrec[G * G * CB / 4];
__device__ uint32_t g_xcnt[G * 160];
__device__ uint32_t g_tflag[160];
__device__ uint32_t g_epoch;

#define STAMP(i)
#define TW(acc, stmt) stmt
#define TWOUT(i, v)

struct TrueT { static constexpr bool value = true; };
struct FalseT { static constexpr bool value = false; };
__device__ __forceinline__ float bf16r(float x) { return __bfloat162float(__float2bfloat16_rn(x)); }
__device__ __forceinline__ float bf_lo(uint32_t u) { return __uint_as_float(u << 16); }
__device__ __forceinline__ float bf_hi(uint32_t u) { return __uint_as_float(u & 0xffff0000u); }
__device__ __forceinline__ uint32_t pack_bf(float lo, float hi) {
    uint32_t r;
    asm("cvt.rn.bf16x2.f32 %0, %1, %2;" : "=r"(r) : "f"(hi), "f"(lo));
    return r;
}
__device__ __forceinline__ uint32_t hmul2_bf(uint32_t a, uint32_t b) {
    uint32_t r;
    asm("mul.rn.bf16x2 %0, %1, %2;" : "=r"(r) : "r"(a), "r"(b));
    return r;
}
__device__ __forceinline__ uint32_t hsub2_bf(uint32_t a, uint32_t b) {
    uint32_t r;
    asm("sub.rn.bf16x2 %0, %1, %2;" : "=r"(r) : "r"(a), "r"(b));
    return r;
}
__device__ __forceinline__ uint32_t smem_u32(const void* p) { return (uint32_t)__cvta_generic_to_shared(p); }
__device__ __forceinline__ uint32_t opaque(uint32_t x) {
    asm volatile("" : "+r"(x));
    return x;
}
__device__ __forceinline__ void trap_if(bool c) {
    asm volatile("{.reg .pred p; setp.ne.u32 p, %0, 0; @p trap;}" ::"r"((uint32_t)c));
}
__device__ __forceinline__ void mbar_init(uint32_t bar, int cnt) {
    asm volatile("mbarrier.init.shared.b64 [%0], %1;" ::"r"(bar), "r"(cnt) : "memory");
}
__device__ __forceinline__ void mbar_arrive(uint32_t bar) {
    asm volatile("mbarrier.arrive.shared.b64 _, [%0];" ::"r"(bar) : "memory");
}
__device__ __forceinline__ void mbar_arrive_if(uint32_t bar, bool pred) {
    asm volatile("{.reg .pred p; setp.ne.u32 p, %1, 0; @p mbarrier.arrive.shared.b64 _, [%0];}" ::"r"(bar), "r"((uint32_t)pred) : "memory");
}
__device__ __forceinline__ void release_if(uint32_t a, uint32_t v, bool pred) {
    asm volatile("{.reg .pred p; setp.ne.u32 p, %2, 0; @p st.relaxed.cta.shared.u8 [%0], %1;}" ::"r"(a), "r"(v), "r"((uint32_t)pred) : "memory");
}
__device__ __forceinline__ uint32_t ld_acq_smem(uint32_t a) {
    uint32_t v;
    asm volatile("ld.relaxed.cta.shared.u32 %0, [%1];" : "=r"(v) : "r"(a) : "memory");
    return v;
}
__device__ __forceinline__ void mbar_expect_tx(uint32_t bar, uint32_t bytes) {
    asm volatile("mbarrier.arrive.expect_tx.shared.b64 _, [%0], %1;" ::"r"(bar), "r"(bytes) : "memory");
}
__device__ __forceinline__ uint32_t mbar_test(uint32_t bar, uint32_t parity) {
    uint32_t ok;
    asm volatile("{.reg .pred p; mbarrier.test_wait.parity.shared.b64 p, [%1], %2; selp.u32 %0, 1, 0, p;}"
                 : "=r"(ok) : "r"(bar), "r"(parity) : "memory");
    return ok;
}
__device__ __forceinline__ void mbar_wait(uint32_t bar, uint32_t parity) {
    asm volatile(
        "{.reg .pred p, q; .reg .u32 c;\n"
        "mbarrier.try_wait.parity.shared.b64 p, [%0], %1;\n"
        "@p bra.uni DONE;\n"
        "mov.u32 c, 0;\n"
        "LOOP:\n"
        "mbarrier.try_wait.parity.shared.b64 p, [%0], %1, 0x4000;\n"
        "@p bra.uni DONE;\n"
        "add.u32 c, c, 1;\n"
        "setp.gt.u32 q, c, 0x100000;\n"
        "@q trap;\n"
        "bra.uni LOOP;\n"
        "DONE:}"
        ::"r"(bar), "r"(parity) : "memory");
}
__device__ __forceinline__ void fence_async_smem() { asm volatile("fence.proxy.async.shared::cta;" ::: "memory"); }
__device__ __forceinline__ void bulk_g2s(uint32_t dst, const void* src, uint32_t bytes, uint32_t bar) {
    asm volatile("cp.async.bulk.shared::cluster.global.mbarrier::complete_tx::bytes [%0], [%1], %2, [%3];"
                 ::"r"(dst), "l"(src), "r"(bytes), "r"(bar) : "memory");
}
__device__ __forceinline__ void bulk_s2g(void* dst, uint32_t src, uint32_t bytes) {
    asm volatile("cp.async.bulk.global.shared::cta.bulk_group [%0], [%1], %2;" ::"l"(dst), "r"(src), "r"(bytes) : "memory");
}
__device__ __forceinline__ void cp16(uint32_t dst, const void* src) {
    asm volatile("cp.async.cg.shared.global [%0], [%1], 16;" ::"r"(dst), "l"(src) : "memory");
}
__device__ __forceinline__ void cp_wait_all() { asm volatile("cp.async.wait_all;" ::: "memory"); }
__device__ __forceinline__ void bar_named(int id, int n) { asm volatile("bar.sync %0, %1;" ::"r"(id), "r"(n) : "memory"); }
__device__ __forceinline__ bool bar_named_or(int id, int n, bool v) {
    uint32_t r;
    asm volatile("{.reg .pred p, q; setp.ne.u32 p, %3, 0; bar.red.or.pred q, %1, %2, p; selp.u32 %0, 1, 0, q;}"
                 : "=r"(r) : "r"(id), "r"(n), "r"((uint32_t)v) : "memory");
    return r;
}
__device__ __forceinline__ uint4 ld_cg_volatile(const uint4* p) {
    uint4 v;
    asm volatile("ld.relaxed.gpu.global.v4.u32 {%0,%1,%2,%3}, [%4];" : "=r"(v.x), "=r"(v.y), "=r"(v.z), "=r"(v.w) : "l"(p) : "memory");
    return v;
}
__device__ __forceinline__ uint32_t ld_acq(const uint32_t* p) {
    uint32_t v;
    asm volatile("ld.acquire.gpu.global.u32 %0, [%1];" : "=r"(v) : "l"(p) : "memory");
    return v;
}
__device__ __forceinline__ uint32_t ld_rlx(const uint32_t* p) {
    uint32_t v;
    asm volatile("ld.relaxed.gpu.global.u32 %0, [%1];" : "=r"(v) : "l"(p) : "memory");
    return v;
}
__device__ __forceinline__ void st_rlx(uint32_t* p, uint32_t v) {
    asm volatile("st.relaxed.gpu.global.u32 [%0], %1;" ::"l"(p), "r"(v) : "memory");
}
__device__ __forceinline__ void fence_gpu() { asm volatile("fence.acq_rel.gpu;" ::: "memory"); }
__device__ __forceinline__ void ldsm_x4(uint32_t* r, uint32_t a) {
    asm volatile("ldmatrix.sync.aligned.m8n8.x4.shared.b16 {%0,%1,%2,%3}, [%4];"
                 : "=r"(r[0]), "=r"(r[1]), "=r"(r[2]), "=r"(r[3]) : "r"(a) : "memory");
}
__device__ __forceinline__ void ldsm_x4_t(uint32_t* r, uint32_t a) {
    asm volatile("ldmatrix.sync.aligned.m8n8.x4.trans.shared.b16 {%0,%1,%2,%3}, [%4];"
                 : "=r"(r[0]), "=r"(r[1]), "=r"(r[2]), "=r"(r[3]) : "r"(a) : "memory");
}
__device__ __forceinline__ void stsm_x4(uint32_t a, const uint32_t* r) {
    asm volatile("stmatrix.sync.aligned.m8n8.x4.shared.b16 [%0], {%1,%2,%3,%4};" ::"r"(a), "r"(r[0]), "r"(r[1]), "r"(r[2]), "r"(r[3]) : "memory");
}
__device__ __forceinline__ void mma16816(float* d, const uint32_t* a, uint32_t b0, uint32_t b1) {
    asm("mma.sync.aligned.m16n8k16.row.col.f32.bf16.bf16.f32 {%0,%1,%2,%3},{%4,%5,%6,%7},{%8,%9},{%0,%1,%2,%3};"
                 : "+f"(d[0]), "+f"(d[1]), "+f"(d[2]), "+f"(d[3])
                 : "r"(a[0]), "r"(a[1]), "r"(a[2]), "r"(a[3]), "r"(b0), "r"(b1));
}
__device__ __forceinline__ void mma1688(float* d, const uint32_t* a, uint32_t b) {
    asm("mma.sync.aligned.m16n8k8.row.col.f32.bf16.bf16.f32 {%0,%1,%2,%3},{%4,%5},{%6},{%0,%1,%2,%3};"
        : "+f"(d[0]), "+f"(d[1]), "+f"(d[2]), "+f"(d[3]) : "r"(a[0]), "r"(a[1]), "r"(b));
}
__device__ __forceinline__ uint32_t hfma2_bf(uint32_t a, uint32_t b, uint32_t c) {
    uint32_t r;
    asm("fma.rn.bf16x2 %0, %1, %2, %3;" : "=r"(r) : "r"(a), "r"(b), "r"(c));
    return r;
}
__device__ __forceinline__ uint4 lds128(uint32_t a) {
    uint4 v;
    asm volatile("ld.shared.v4.u32 {%0,%1,%2,%3}, [%4];" : "=r"(v.x), "=r"(v.y), "=r"(v.z), "=r"(v.w) : "r"(a) : "memory");
    return v;
}
__device__ __forceinline__ uint2 lds64(uint32_t a) {
    uint2 v;
    asm volatile("ld.shared.v2.u32 {%0,%1}, [%2];" : "=r"(v.x), "=r"(v.y) : "r"(a) : "memory");
    return v;
}
__device__ __forceinline__ uint32_t lds32(uint32_t a) {
    uint32_t v;
    asm volatile("ld.shared.u32 %0, [%1];" : "=r"(v) : "r"(a) : "memory");
    return v;
}
__device__ __forceinline__ uint32_t lds16(uint32_t a) {
    uint32_t v;
    asm volatile("{.reg .u16 t; ld.shared.u16 t, [%1]; cvt.u32.u16 %0, t;}" : "=r"(v) : "r"(a) : "memory");
    return v;
}
__device__ __forceinline__ void sts16(uint32_t a, uint32_t x) {
    asm volatile("{.reg .u16 t; cvt.u16.u32 t, %1; st.shared.u16 [%0], t;}" ::"r"(a), "r"(x) : "memory");
}
__device__ __forceinline__ void sts32(uint32_t a, uint32_t x) {
    asm volatile("st.shared.u32 [%0], %1;" ::"r"(a), "r"(x) : "memory");
}
__device__ __forceinline__ void sts32f(uint32_t a, float x) {
    asm volatile("st.shared.f32 [%0], %1;" ::"r"(a), "f"(x) : "memory");
}
__device__ __forceinline__ uint32_t atoms_inc(uint32_t a) {
    uint32_t v;
    asm volatile("atom.shared.add.u32 %0, [%1], 1;" : "=r"(v) : "r"(a) : "memory");
    return v;
}
__device__ __forceinline__ uint32_t atoms_inc_if(uint32_t a, bool pred) {
    uint32_t v = 0xffffffffu;
    asm volatile("{.reg .pred p; setp.ne.u32 p, %2, 0; @p atom.shared.add.u32 %0, [%1], 1;}" : "+r"(v) : "r"(a), "r"((uint32_t)pred));
    return v;
}
__device__ __forceinline__ int warp_scan(int v, int lane) {
#pragma unroll
    for (int o = 1; o < 32; o <<= 1) {
        int t = __shfl_up_sync(~0u, v, o);
        if (lane >= o) v += t;
    }
    return v;
}

constexpr int NCW = 2;
constexpr int NS = 16;
constexpr int CH = 4;
constexpr int NRB = 4;
constexpr int CAPK = 384;
constexpr int KB = 160;
constexpr int RPT = 19;
constexpr int SVROW = 528;
constexpr int WROW = 144;
constexpr int TPC = (NTILE + G - 1) / G;

constexpr int SM_RING = 0;
constexpr int SM_RT = SM_RING + NS * 8192;
constexpr int SM_EX = SM_RT + NCW * NRB * CH * 512;
constexpr int SM_SORT = SM_EX + NCW * 2 * 3 * 288;
constexpr int SM_PDST = SM_SORT + CAPK * KB;
constexpr int SM_GCNT = SM_PDST + NPG * 128;
constexpr int SM_NCNT = SM_GCNT + 160 * 4;
constexpr int SM_KST = SM_NCNT + 96 * 4;
constexpr int SM_FLAG = SM_KST + 104 * 4;
constexpr int SM_ONES = SM_FLAG + 16;
constexpr int SM_REL = SM_ONES + CH * KB;
constexpr int SM_BAR = SM_REL + (1 + NCW) * 64;
constexpr int SMEM_BYTES = SM_BAR + (NCW * NRB + 2) * 8;
constexpr int SM_POS = SM_RING;
constexpr int SM_SV = SM_POS + 60160;
constexpr int SM_W = SM_SV + TPC * 16 * SVROW;
constexpr int SM_RAW = SM_W + 2 * 64 * WROW;
constexpr int SM_BINS = SM_SORT;
constexpr int CST_SLOT = 8;
constexpr int SM_CST = SM_RING + CST_SLOT * 8192;
static_assert(SM_CST >= SM_SV && SM_CST + 44 * 512 <= SM_W, "constants");
static_assert(RT_N * 8 <= G * 128 && (SM_ONES - SM_GCNT) / 4 >= ET && SM_RAW + RPT * ET * 4 <= SM_SORT && G * CB * 4 <= CAPK * KB && G == 132 && TPC == 5, "phase 1 map");
static_assert(NPG * 1024 <= NS * 8192, "slow path accumulators live in the ring");
static_assert(NPG <= 96 && SMEM_BYTES <= 232448, "sizes");

#define WG_FENCE() asm volatile("wgmma.fence.sync.aligned;" ::: "memory")
#define WG_COMMIT() asm volatile("wgmma.commit_group.sync.aligned;" ::: "memory")
#define WG_WAIT(n) asm volatile("wgmma.wait_group.sync.aligned %0;" ::"n"(n) : "memory")
#define F8(d, o) "+f"(d[o + 0]), "+f"(d[o + 1]), "+f"(d[o + 2]), "+f"(d[o + 3]), "+f"(d[o + 4]), "+f"(d[o + 5]), "+f"(d[o + 6]), "+f"(d[o + 7])

#define O8(d, o) "=f"(d[o + 0]), "=f"(d[o + 1]), "=f"(d[o + 2]), "=f"(d[o + 3]), "=f"(d[o + 4]), "=f"(d[o + 5]), "=f"(d[o + 6]), "=f"(d[o + 7])
#define KSTEP_ASM(ACC)                                                                                              \
    "{.reg .b64 d, r; .reg .b32 t;\n"                                                                               \
    "or.b32 t, %60, 64; mov.b64 d, {t, 0x40000040};\n"                                                              \
    "wgmma.mma_async.sync.aligned.m64n64k16.f32.bf16.bf16 "                                                         \
    "{%0,%1,%2,%3,%4,%5,%6,%7,%8,%9,%10,%11,%12,%13,%14,%15,%16,%17,%18,%19,%20,%21,%22,%23,%24,%25,%26,%27,%28,"   \
    "%29,%30,%31},{%56,%57,%58,%59},d," ACC ",1,1,1;\n"                                                             \
    "mov.b64 r, {%61, 8}; or.b32 t, %60, 192; mov.b64 d, {t, 0x40000040};\n"                                        \
    "wgmma.mma_async.sync.aligned.m64n16k16.f32.bf16.bf16 {%32,%33,%34,%35,%36,%37,%38,%39},d,r," ACC ",1,1,1,1;\n" \
    "or.b32 t, %60, 320; mov.b64 d, {t, 0x40000040};\n"                                                             \
    "wgmma.mma_async.sync.aligned.m64n16k16.f32.bf16.bf16 {%40,%41,%42,%43,%44,%45,%46,%47},d,r," ACC ",1,1,1,1;\n" \
    "or.b32 t, %60, 448; mov.b64 d, {t, 0x40000040};\n"                                                             \
    "wgmma.mma_async.sync.aligned.m64n16k16.f32.bf16.bf16 {%48,%49,%50,%51,%52,%53,%54,%55},d,r," ACC ",1,1,1,1;}"
template <bool ACC>
__device__ __forceinline__ void kstep_mma(float* T, float* U, const uint32_t* a, uint32_t ds, uint32_t dr) {
    if (ACC)
        asm volatile(KSTEP_ASM("1")
                     : F8(T, 0), F8(T, 8), F8(T, 16), F8(T, 24), F8(U, 0), F8(U, 8), F8(U, 16)
                     : "r"(a[0]), "r"(a[1]), "r"(a[2]), "r"(a[3]), "r"(ds), "r"(dr) : "memory");
    else
        asm volatile(KSTEP_ASM("0")
                     : O8(T, 0), O8(T, 8), O8(T, 16), O8(T, 24), O8(U, 0), O8(U, 8), O8(U, 16)
                     : "r"(a[0]), "r"(a[1]), "r"(a[2]), "r"(a[3]), "r"(ds), "r"(dr) : "memory");
}
template <int N> struct IntT { static constexpr int value = N; };

__device__ __forceinline__ void wait_table(uint32_t tag, int lane) {
    for (int it = 0;; it++) {
        bool ok = true;
#pragma unroll
        for (int j = 0; j < 5; j++) {
            const int b = j * 32 + lane;
            if (b < G) ok &= ld_rlx(&g_tflag[b]) == tag;
        }
        if (__all_sync(~0u, ok)) break;
        trap_if(it > (1 << 22));
    }
    fence_gpu();
}

__device__ __forceinline__ void table_tile(unsigned char* sm, int tl, int lane) {
    constexpr uint32_t sb = 1024;
    const int tile = blockIdx.x + tl * G;
    if (tile >= NTILE) return;
    const uint32_t frag = sb + SM_SV + (tl * 16 + (lane & 15)) * SVROW + (lane >> 4) * 16;
    uint32_t a[4][4];
#pragma unroll
    for (int kk = 0; kk < 4; kk++) ldsm_x4(a[kk], frag + kk * 32);
    float acc[8][4];
#pragma unroll
    for (int m = 0; m < 2; m++) {
#pragma unroll
        for (int nt = 0; nt < 8; nt++) acc[nt][0] = acc[nt][1] = acc[nt][2] = acc[nt][3] = 0.f;
        const uint32_t wb = sb + SM_W + m * 64 * WROW + (lane & 15) * WROW + (lane >> 4) * 16;
#pragma unroll
        for (int kk = 0; kk < 4; kk++) {
#pragma unroll
            for (int np = 0; np < 4; np++) {
                uint32_t b[4];
                ldsm_x4_t(b, wb + kk * 16 * WROW + np * 32);
                mma16816(acc[2 * np], a[kk], b[0], b[1]);
                mma16816(acc[2 * np + 1], a[kk], b[2], b[3]);
            }
        }
        if (m == 0) {
#pragma unroll
            for (int nt = 0; nt < 8; nt++) {
                float t[4];
#pragma unroll
                for (int i = 0; i < 4; i++) {
                    const float x = bf16r(acc[nt][i]);
                    t[i] = __fdividef(x, 1.0f + __expf(-x));
                }
                a[nt >> 1][(nt & 1) * 2] = pack_bf(t[0], t[1]);
                a[nt >> 1][(nt & 1) * 2 + 1] = pack_bf(t[2], t[3]);
            }
#pragma unroll
            for (int kk = 0; kk < 4; kk++) stsm_x4(frag + kk * 32, a[kk]);
        }
    }
#pragma unroll
    for (int kk = 0; kk < 4; kk++) {
        const uint32_t ph[4] = {pack_bf(acc[2 * kk][0], acc[2 * kk][1]), pack_bf(acc[2 * kk][2], acc[2 * kk][3]),
                                pack_bf(acc[2 * kk + 1][0], acc[2 * kk + 1][1]), pack_bf(acc[2 * kk + 1][2], acc[2 * kk + 1][3])};
        uint32_t v[3][4];
#pragma unroll
        for (int x = 0; x < 3; x++) ldsm_x4(v[x], frag + 128 + x * 128 + kk * 32);
#pragma unroll
        for (int x = 0; x < 3; x++) {
#pragma unroll
            for (int i = 0; i < 4; i++) v[x][i] = hmul2_bf(v[x][i], ph[i]);
            stsm_x4(frag + 128 + x * 128 + kk * 32, v[x]);
        }
    }
    __syncwarp();
    unsigned char* o = arena_base() + (lane >> 4) * WIN + tile * 4096 + (lane & 15) * 16;
#pragma unroll
    for (int r = 0; r < 16; r++)
        *reinterpret_cast<uint4*>(o + r * 256) = *reinterpret_cast<const uint4*>(sm + SM_SV + (tl * 16 + r) * SVROW + lane * 16);
}

__device__ __forceinline__ bool edge_geom(uint32_t axy, uint32_t az, uint32_t bxy, uint32_t bz, uint32_t& w1, uint32_t& w2) {
    const uint32_t rxy = hsub2_bf(axy, bxy), rz = hsub2_bf(az, bz);
    const uint32_t qxy = hmul2_bf(rxy, rxy), qz = hmul2_bf(rz, rz);
    float q = __uint_as_float(pack_bf(0.f, bf_lo(qxy) + bf_hi(qxy) + bf_lo(qz)));
    q = __uint_as_float(pack_bf(0.f, q + 1e-08f));
    float d, rd;
    asm("sqrt.approx.ftz.f32 %0, %1;" : "=f"(d) : "f"(q));
    const uint32_t du = pack_bf(0.f, d);
    d = __uint_as_float(du);
    asm("rcp.approx.ftz.f32 %0, %1;" : "=f"(rd) : "f"(d));
    w1 = __byte_perm(du, pack_bf(0.f, bf_lo(rxy) * rd), 0x7632);
    w2 = pack_bf(bf_hi(rxy) * rd, bf_lo(rz) * rd);
    return d < D_ACTIVE;
}

__device__ __noinline__ void slow_group(unsigned char* sm, const __nv_bfloat16* sv, const __nv_bfloat16* pos,
                                        const int* src, const int* dst, const __nv_bfloat16* w2,
                                        const __nv_bfloat16* wr, __nv_bfloat16* out, int npg) {
    const int tid = threadIdx.x, lane = tid & 31, grp = blockIdx.x;
    float* acc = reinterpret_cast<float*>(sm);
    for (int i = tid; i < npg * 256; i += CT) acc[i] = 0.f;
    bar_named(1, CT);
    const unsigned short* p16 = reinterpret_cast<const unsigned short*>(pos);
    static_assert(NE % 32 == 0, "");
    for (int e0 = tid - lane; e0 < NE; e0 += CT) {
        const int b = dst[e0 + lane], a = src[e0 + lane];
        uint32_t w1 = 0, w2r = 0;
        bool act = false;
        if (b % G == grp)
            act = edge_geom(p16[3 * a] | (p16[3 * a + 1] << 16), p16[3 * a + 2], p16[3 * b] | (p16[3 * b + 1] << 16),
                            p16[3 * b + 2], w1, w2r);
        for (uint32_t todo = __ballot_sync(~0u, act); todo; todo &= todo - 1) {
            const int l = __ffs(todo) - 1;
            const uint32_t ea = __shfl_sync(~0u, a, l), eb = __shfl_sync(~0u, b, l);
            const uint32_t e1 = __shfl_sync(~0u, w1, l), e2 = __shfl_sync(~0u, w2r, l);
            const unsigned short* row = reinterpret_cast<const unsigned short*>(arena_base()) + (size_t)ea * 128;
            const unsigned short* R = reinterpret_cast<const unsigned short*>(arena_base() + RT_OFF) + ((e1 & 0xffff) - RT_LO + 1) * 16;
            const float rh[3] = {bf_hi(e1), bf_lo(e2), bf_hi(e2)};
            float* o = acc + (eb / G) * 256;
            for (int c = lane; c < 64; c += 32) {
                float ps = 0.f, pr = 0.f, ws = 0.f, wv = 0.f, wvr = 0.f;
                for (int j = 0; j < 64; j++) {
                    const float h = bf_lo(__ldcg(row + j));
                    ps += h * __bfloat162float(w2[j * 192 + c]);
                    pr += h * __bfloat162float(w2[j * 192 + 128 + c]);
                }
                for (int k = 0; k < 16; k++) {
                    const float r = bf_lo(__ldcg(R + k));
                    ws += r * __bfloat162float(wr[k * 192 + c]);
                    wv += r * __bfloat162float(wr[k * 192 + 64 + c]);
                    wvr += r * __bfloat162float(wr[k * 192 + 128 + c]);
                }
                atomicAdd(o + c, ps * ws);
                for (int x = 0; x < 3; x++)
                    atomicAdd(o + 64 + x * 64 + c, bf_lo(__ldcg(row + (x ? WIN / 2 - 64 : 64) + x * 64 + c)) * wv + pr * wvr * rh[x]);
            }
        }
    }
    bar_named(1, CT);
    for (int i = tid; i < npg * 256; i += CT) {
        const size_t o = (size_t)((i >> 8) * G + grp) * 256 + (i & 255);
        out[o] = __float2bfloat16_rn(__bfloat162float(sv[o]) + acc[i]);
    }
}

template <int MODE>
__global__ void __launch_bounds__(THREADS, 1)
painn_kernel(const __nv_bfloat16* __restrict__ sv, const __nv_bfloat16* __restrict__ pos,
             const int* __restrict__ src, const int* __restrict__ dst,
             const __nv_bfloat16* __restrict__ freqs, const __nv_bfloat16* __restrict__ w1,
             const __nv_bfloat16* __restrict__ w2, const __nv_bfloat16* __restrict__ wr,
             __nv_bfloat16* __restrict__ out) {
    extern __shared__ __align__(1024) unsigned char sm[];
    const int tid = threadIdx.x, lane = tid & 31;
    const int warp = __shfl_sync(~0u, tid >> 5, 0), wg = warp >> 2;
    const int blk = blockIdx.x;
    constexpr uint32_t sb = 1024;
    const uint32_t bar_pos = sb + SM_BAR + NCW * NRB * 8;
    STAMP(0);

    const int npg = (NN - blk + G - 1) / G;
    uint32_t tag;
    bool slow = false;
    if (warp >= 11) {
        const int tw = warp - 11, tt = tid - ET;
        trap_if(smem_u32(sm) != sb);
        if (tid == THREADS - 32) {
            for (int i = 0; i < NCW * NRB; i++) mbar_init(sb + SM_BAR + i * 8, 32);
            mbar_init(bar_pos, 1);
            mbar_init(bar_pos + 8, NCW * 128);
            if (MODE != 1) {
                fence_async_smem();
                mbar_expect_tx(bar_pos, NN * 6);
                bulk_g2s(sb + SM_POS, pos, NN * 6, bar_pos);
            }
        }
        asm volatile("bar.arrive 6, %0;" ::"n"(THREADS) : "memory");
        tag = ld_rlx(&g_epoch) + 1u;
        if (MODE != 2) {
            const uint32_t f2 = __ldg(reinterpret_cast<const uint32_t*>(freqs) + (tt & 7));
            for (int i = tt; i < 1024; i += 160) {
                const int m = i >> 9, r = (i >> 3) & 63, c = i & 7;
                cp16(sb + SM_W + (m * 64 + r) * WROW + c * 16, m == 0 ? w1 + r * 64 + c * 8 : w2 + r * 192 + 64 + c * 8);
            }
            asm volatile("cp.async.commit_group;" ::: "memory");
            const int tile = blk + tw * G;
            if (tile < NTILE) {
#pragma unroll
                for (int i = 0; i < 16; i++)
                    cp16(sb + SM_SV + (tw * 16 + i) * SVROW + lane * 16, sv + (size_t)(tile * 16 + i) * 256 + lane * 8);
            }
            asm volatile("cp.async.commit_group;" ::: "memory");
            if (blk == G - 1 && tt < 8) reinterpret_cast<uint32_t*>(arena_base() + RT_OFF)[tt] = 0u;
            if (const int i = blk * 128 + tt; tt < 128 && i < RT_N * 8) {
                const float d = __uint_as_float((uint32_t)(RT_LO + (i >> 3)) << 16);
                const float arg = bf16r(__fdividef(bf16r(3.14159265358979f * d), 5.0f));
                const float fc = bf16r(0.5f * bf16r(bf16r(cosf(arg)) + 1.0f));
                float sn[2] = {bf16r(d * bf_lo(f2)), bf16r(d * bf_hi(f2))};
#pragma unroll 1
                for (int k = 0; k < 2; k++) {
                    const float x = sinf(sn[0]);
                    sn[0] = sn[1];
                    sn[1] = x;
                }
                const float r0 = bf16r(__fdividef(bf16r(sn[0]), d)) * fc;
                const float r1 = bf16r(__fdividef(bf16r(sn[1]), d)) * fc;
                reinterpret_cast<uint32_t*>(arena_base() + RT_OFF)[i + 8] = pack_bf(r0, r1);
            }
            STAMP(10);
            asm volatile("cp.async.wait_group 1;" ::: "memory");
            bar_named(2, 160);
            cp_wait_all();
            __syncwarp();
            STAMP(1);
            table_tile(sm, tw, lane);
            STAMP(2);
            fence_gpu();
            bar_named(2, 160);
            if (tid == ET) st_rlx(&g_tflag[blk], tag);
            STAMP(3);
        }
        if (MODE != 1 && wg == 3) {
            const int w = warp & 3, g = lane >> 2, q = lane & 3;
            uint4* cst = reinterpret_cast<uint4*>(sm + SM_CST) + lane;
            auto quad = [&](const uint32_t* x, int koff) {
                const uint32_t a0 = __ldg(x + koff * 96), a1 = __ldg(x + (koff + 1) * 96);
                const uint32_t b0 = __ldg(x + (koff + 8) * 96), b1 = __ldg(x + (koff + 9) * 96);
                return make_uint4(__byte_perm(a0, a1, 0x5410), __byte_perm(a0, a1, 0x7632),
                                  __byte_perm(b0, b1, 0x5410), __byte_perm(b0, b1, 0x7632));
            };
#pragma unroll
            for (int v = 0; v < 2; v++) {
#pragma unroll
                for (int kk = 0; kk < 4; kk++)
                    cst[(v * 20 + w * 4 + kk) * 32] = quad(reinterpret_cast<const uint32_t*>(w2 + v * 128) + w * 8 + g, 16 * kk + 2 * q);
                cst[(v * 20 + 16 + w) * 32] = quad(reinterpret_cast<const uint32_t*>(wr + v * 128) + w * 8 + g, 2 * q);
            }
            const unsigned short* wrp = reinterpret_cast<const unsigned short*>(wr) + 64 + 16 * w + g + 2 * q * 192;
            uint32_t x[4];
#pragma unroll
            for (int i = 0; i < 4; i++) {
                const unsigned short* y = wrp + (i >> 1) * 8 * 192 + (i & 1) * 8;
                x[i] = (uint32_t)__ldg(y) | ((uint32_t)__ldg(y + 192) << 16);
            }
            cst[(40 + w) * 32] = make_uint4(x[0], x[1], x[2], x[3]);
        }
    } else {
    uint32_t es[EPT], ed[EPT];
    bool tail = false;
    if (MODE != 2) {
#pragma unroll
        for (int r = 0; r < EV; r++) {
            const int gi = (blk * EV + r) * ET + tid;
            const int4 d4 = __ldcs(reinterpret_cast<const int4*>(dst) + gi);
            const int4 s4 = __ldcs(reinterpret_cast<const int4*>(src) + gi);
            es[4 * r] = s4.x; es[4 * r + 1] = s4.y; es[4 * r + 2] = s4.z; es[4 * r + 3] = s4.w;
            ed[4 * r] = d4.x; ed[4 * r + 1] = d4.y; ed[4 * r + 2] = d4.z; ed[4 * r + 3] = d4.w;
        }
        const int te = E_VEC / 2 + blk * E_TAIL + tid;
        tail = tid < E_TAIL && te < NE / 2;
        int2 s2 = make_int2(0, 0), d2 = make_int2(0, 0);
        if (tail) {
            d2 = __ldcs(reinterpret_cast<const int2*>(dst) + te);
            s2 = __ldcs(reinterpret_cast<const int2*>(src) + te);
        }
        es[EPT - 2] = s2.x; es[EPT - 1] = s2.y;
        ed[EPT - 2] = d2.x; ed[EPT - 1] = d2.y;
    }
    tag = ld_rlx(&g_epoch) + 1u;
    if (MODE != 1) {
        if (tid >= 160 && tid < 160 + 48) asm volatile("prefetch.global.L2 [%0];" ::"l"(wr + (tid - 160) * 64));
        if (tid >= 224) asm volatile("prefetch.global.L2 [%0];" ::"l"(w2 + ((tid - 224) >> 1) * 192 + (tid & 1) * 128));
    }
    sts32(sb + SM_GCNT + tid * 4, 0u);
    if (const int i = tid + ET; i < (SM_BAR - SM_GCNT) / 4)
        sts32(sb + SM_GCNT + i * 4, i >= (SM_ONES - SM_GCNT) / 4 && i < (SM_REL - SM_GCNT) / 4 ? 0x3f803f80u : 0u);
    bar_named(6, THREADS);
    if (MODE != 2) {
        uint32_t rk[EPT];
#pragma unroll
        for (int i = 0; i < EPT; i++) {
            const uint32_t dl = ed[i] / G;
            ed[i] -= dl * G;
            es[i] |= (dl << 14) | (tag << 21);
            rk[i] = atoms_inc_if(sb + SM_GCNT + ed[i] * 4, i < EPT - 2 || tail);
        }
#pragma unroll
        for (int i = 0; i < EPT; i++)
            if (rk[i] < CB) reinterpret_cast<uint32_t*>(sm + SM_BINS)[ed[i] * CB + rk[i]] = es[i];
        STAMP(2);
        bar_named(1, ET);
        {
            const uint32_t c = lane & 15;
            uint32_t cnt[6];
            uint4 v[6];
#pragma unroll
            for (int j = 0; j < 6; j++) {
                const uint32_t g = (j * 11 + warp) * 2 + (lane >> 4);
                cnt[j] = reinterpret_cast<const uint32_t*>(sm + SM_GCNT)[g];
                v[j] = reinterpret_cast<const uint4*>(sm + SM_BINS)[g * (CB / 4) + c];
            }
            auto put = [&](uint4 x, uint32_t g, uint32_t k, uint32_t n) {
                if (k * 4 >= n) x.x = 0;
                if (k * 4 + 1 >= n) x.y = 0;
                if (k * 4 + 2 >= n) x.z = 0;
                if (k * 4 + 3 >= n) x.w = 0;
                __stcg(&g_xrec[(g * G + blk) * (CB / 4) + k], x);
            };
            bool big = false;
#pragma unroll
            for (int j = 0; j < 6; j++) {
                if ((c & 14) * 4 < cnt[j]) put(v[j], (j * 11 + warp) * 2 + (lane >> 4), c, cnt[j]);
                big |= cnt[j] > 64;
            }
            if (big) {
#pragma unroll 1
                for (int j = 0; j < 6; j++) {
                    const uint32_t g = (j * 11 + warp) * 2 + (lane >> 4);
                    const uint32_t n = reinterpret_cast<const uint32_t*>(sm + SM_GCNT)[g];
                    if (n > 64 && c < CB / 4 - 16) put(reinterpret_cast<const uint4*>(sm + SM_BINS)[g * (CB / 4) + 16 + c], g, 16 + c, n);
                }
            }
            if (tid < 136) st_rlx(&g_xcnt[blk * 160 + tid], reinterpret_cast<const uint32_t*>(sm + SM_GCNT)[tid] | (tag << 21));
        }
        STAMP(3);
        if (MODE != 1) bar_named(1, ET);
    }

    if (MODE != 1) {
        for (int i = tid; i < CAPK * KB / 16; i += ET) reinterpret_cast<uint4*>(sm + SM_SORT)[i] = make_uint4(0, 0, 0, 0);
        mbar_wait(bar_pos, 0);
        for (int i = tid; i < npg * 16; i += ET) {
            const unsigned short* pn = reinterpret_cast<const unsigned short*>(sm + SM_POS) + ((i >> 4) * G + blk) * 3;
            reinterpret_cast<uint2*>(sm + SM_PDST)[i] = make_uint2(pn[0] | (pn[1] << 16), pn[2]);
        }
        bar_named(1, ET);
    }
    if (MODE != 1) {
    STAMP(4);
    uint32_t r0[RPT], w1e[RPT], w2e[RPT], rk[RPT];
    {
        uint32_t mine = tag << 21;
        for (int it = 0;; it++) {
            if (lane < 12) mine = ld_rlx(&g_xcnt[(warp * 12 + lane) * 160 + blk]);
            if (__all_sync(~0u, (mine >> 21) == tag)) break;
            trap_if(it > (1 << 22));
        }
        STAMP(5);
        mine &= 0x1fffff;
        const uint32_t h = lane >> 4, c = lane & 15;
        const uint4* xr = g_xrec + (blk * G + warp * 12 + h) * (CB / 4) + c;
        uint4 v[6];
        uint32_t cnt[6];
#pragma unroll
        for (int j = 0; j < 6; j++) {
            cnt[j] = __shfl_sync(~0u, mine, 2 * j + h);
            if (c * 4 < cnt[j]) v[j] = ld_cg_volatile(xr + j * 2 * (CB / 4));
        }
        const uint32_t nch = (mine + 3) >> 2, incl = warp_scan(nch, lane);
        const uint32_t total = __shfl_sync(~0u, incl, 31) * 4, base = incl - nch;
        slow = total > RPT * 32 || __any_sync(~0u, mine > CB);
        uint4* raw = reinterpret_cast<uint4*>(sm + SM_RAW) + warp * (RPT * 8);
        auto valid = [&](const uint4& x, uint32_t k, uint32_t n) {
            return (x.x >> 21) == tag && (k * 4 + 1 >= n || (x.y >> 21) == tag) && (k * 4 + 2 >= n || (x.z >> 21) == tag) &&
                   (k * 4 + 3 >= n || (x.w >> 21) == tag);
        };
        for (int it = 0;; it++) {
            bool redo = false;
#pragma unroll
            for (int j = 0; j < 6; j++) {
                if (c * 4 < cnt[j] && !valid(v[j], c, cnt[j])) {
                    v[j] = ld_cg_volatile(xr + j * 2 * (CB / 4));
                    redo = true;
                }
            }
            if (!__any_sync(~0u, redo)) break;
            trap_if(it > (1 << 22));
        }
        STAMP(1);
        if (!slow) {
#pragma unroll
            for (int j = 0; j < 6; j++) {
                const uint32_t o = __shfl_sync(~0u, base, 2 * j + h);
                if (c * 4 < cnt[j]) raw[o + c] = v[j];
            }
            if (__any_sync(~0u, mine > 64)) {
#pragma unroll 1
                for (int j = 0; j < 6; j++) {
                    const uint32_t o = __shfl_sync(~0u, base, 2 * j + h), n = __shfl_sync(~0u, mine, 2 * j + h);
                    if ((16 + c) * 4 < n) {
                        uint4 x;
                        for (int it = 0;; it++) {
                            x = ld_cg_volatile(xr + j * 2 * (CB / 4) + 16);
                            if (valid(x, 16 + c, n)) break;
                            trap_if(it > (1 << 22));
                        }
                        raw[o + 16 + c] = x;
                    }
                }
            }
            __syncwarp();
#pragma unroll
            for (int i = 0; i < RPT; i++) r0[i] = i * 32 + lane < total ? reinterpret_cast<const uint32_t*>(raw)[i * 32 + lane] : 0u;
#pragma unroll
            for (int i = 0; i < RPT; i++) {
                rk[i] = 0xffffffffu;
                if (i < 13 || i * 32 < total) {
                    const uint32_t a = r0[i] & 0x3fff, dl = (r0[i] >> 14) & 127;
                    const uint32_t* pa = reinterpret_cast<const uint32_t*>(sm + SM_POS + ((a * 6) & ~3u));
                    const uint32_t a0 = pa[0], a1 = pa[1];
                    const uint2 pb = reinterpret_cast<const uint2*>(sm + SM_PDST)[dl * 16 + (lane & 15)];
                    const bool act = edge_geom(__funnelshift_r(a0, a1, a << 4), __funnelshift_r(a1, 0u, a << 4), pb.x, pb.y, w1e[i], w2e[i]);
                    rk[i] = atoms_inc_if(sb + SM_NCNT + dl * 4, act && (r0[i] >> 21) == tag);
                }
            }
        }
    }
    STAMP(6);
    slow = bar_named_or(1, ET, slow);
    if (tag == TAGMAX && !slow)
        for (int i = tid; i < G * CB / 4; i += ET) g_xrec[blk * G * (CB / 4) + i] = make_uint4(0, 0, 0, 0);
    if (!slow) {
        STAMP(10);
        int tot_k;
        {
            int k[4], s = 0;
#pragma unroll
            for (int j = 0; j < 3; j++) {
                k[j] = s;
                s += (reinterpret_cast<const uint32_t*>(sm + SM_NCNT)[lane * 3 + j] + 15) >> 4;
            }
            k[3] = s;
            const int incl = warp_scan(s, lane);
            tot_k = __shfl_sync(~0u, incl, 31);
#pragma unroll
            for (int j = 0; j < 3; j++)
                reinterpret_cast<uint32_t*>(sm + SM_KST)[lane * 3 + j] = (incl - s + k[j]) | ((incl - s + k[j + 1]) << 10);
            __syncwarp();
        }
        slow = tot_k > CAPK - CH;
        if (!slow) {
            uint32_t ks[RPT];
#pragma unroll
            for (int i = 0; i < RPT; i++) ks[i] = reinterpret_cast<const uint32_t*>(sm + SM_KST)[(r0[i] >> 14) & 127] & 1023;
#pragma unroll
            for (int i = 0; i < RPT; i++) {
                if (rk[i] != 0xffffffffu) {
                    const uint32_t e = rk[i] & 15;
                    unsigned short* kb = reinterpret_cast<unsigned short*>(sm + SM_SORT + (ks[i] + (rk[i] >> 4)) * KB);
                    const uint32_t pe = 4 * ((e & 7) >> 1) + (e & 1) + 2 * (e >> 3);
                    kb[e] = (r0[i] & 0x3fff) + 1;
                    kb[16 + e] = w1e[i] - (RT_LO - 1);
                    kb[32 + pe] = w1e[i] >> 16;
                    kb[48 + pe] = w2e[i];
                    kb[64 + pe] = w2e[i] >> 16;
                }
            }
        }
    }
    if (tid == 0) sts32(sb + SM_FLAG, slow);
    STAMP(7);
    }
    }
    if (MODE == 1) return;

    if (wg == 3) {
        const int w = (warp >> 1) & 1;
        asm volatile("setmaxnreg.dec.sync.aligned.u32 56;");
        wait_table(tag, lane);
        STAMP(4);
        bar_named(5, THREADS);
        if (MODE == 0 && blk == 0 && tid == CT) g_epoch = tag % TAGMAX;
        if (lds32(sb + SM_FLAG) == 0) {
            const uint64_t ab = reinterpret_cast<uint64_t>(arena_base());
            const uint32_t ahi = (uint32_t)((ab + (lane >> 4) * WIN) >> 32);
            const uint32_t acst = (uint32_t)(ab + (lane >> 4) * WIN) | ((lane & 15) * 16);
            const uint32_t rlo = (uint32_t)(ab + RT_OFF) + (lane & 1) * 16, rhi = (uint32_t)(ab >> 32);
            const uint32_t dlane = __shfl_sync(~0u, sb + SM_RING + (lane >> 3) * 2048 + (lane & 7) * 16, lane);
            const uint32_t lf = __shfl_sync(~0u, lane, lane);
            const uint32_t rlane = sb + SM_RT + w * NRB * CH * 512 + (lane & 1) * 128 + (lane >> 4) * 256 + ((lane >> 1) & 7) * 16;
            const unsigned char* dlds = sm + SM_SORT + 32 + (lane >> 1) * 2;
            STAMP(8);
            uint32_t tn = 0, tend = 0;
            int n = w - NCW;
            auto next_chunk = [&]() {
                tn += CH;
                while (tn >= tend && n + NCW < npg) {
                    n += NCW;
                    const uint32_t r = reinterpret_cast<const uint32_t*>(sm + SM_KST)[n];
                    tn = r & 1023;
                    tend = r >> 10;
                }
            };
            const uint32_t rel_lane = sb + SM_REL + (lf == 31 ? (1 + w) * 64 : 0);
            uint32_t di[CH];
            auto fetch_d = [&]() {
#pragma unroll
                for (int i = 0; i < CH; i++) di[i] = *reinterpret_cast<const unsigned short*>(dlds + (tn + i) * KB);
            };
            auto load_r = [&](uint32_t buf) {
#pragma unroll
                for (int i = 0; i < CH; i++) {
                    if (tn + i < tend)
                        asm volatile("{.reg .b64 a; mov.b64 a, {%1, %2}; cp.async.ca.shared.global [%0], [a], 16;}"
                                     ::"r"(rlane + (buf * CH + i) * 512), "r"(rlo + di[i] * 32), "r"(rhi));
                }
            };
            auto gather = [&](uint32_t dst, uint32_t sw, int hi) {
                asm volatile("{.reg .b64 a; mov.b64 a, {%1, %2}; cp.async.cg.shared.global [%0], [a + -256], 16;}"
                             ::"r"(dst), "r"(__byte_perm(sw, acst, hi ? 0x7324 : 0x7104)), "r"(ahi));
            };
            auto gather_if = [&](uint32_t dst, uint32_t sw, int hi) {
                asm volatile("{.reg .b64 a; .reg .pred p; setp.gt.u32 p, %3, %4; mov.b64 a, {%1, %2};\n"
                             "@p cp.async.cg.shared.global [%0], [a + -256], 16;}"
                             ::"r"(dst), "r"(__byte_perm(sw, acst, hi ? 0x7324 : 0x7104)), "r"(ahi), "r"(sw), "r"(hi ? 0xffffu : 0u));
            };
            const unsigned char* slds = sm + SM_SORT + __shfl_sync(~0u, (tid >> 9), lane);
            next_chunk();
            uint32_t m = warp & 1;
            if (m) {
                next_chunk();
            } else {
                fetch_d();
                load_r(0);
            }
            uint32_t tw0 = 0, tw1 = 0, tw2 = 0;
            while (tn < tend) {
                const uint32_t t = tn, rem = tend - tn;
                uint4 sw[CH][2];
#pragma unroll
                for (int i = 0; i < CH; i++) {
                    sw[i][0] = *reinterpret_cast<const uint4*>(slds + (t + i) * KB);
                    sw[i][1] = *reinterpret_cast<const uint4*>(slds + (t + i) * KB + 16);
                }
                const uint32_t fbar = sb + SM_BAR + (w * NRB + (m & (NRB - 1))) * 8;
                next_chunk();
                fetch_d();
                m++;
                const uint32_t tl = lf == 31 ? m * 4 : t + lf;
                const uint32_t ctr = rel_lane + (tl & (NS - 1)) * 4;
                const uint32_t need = (tl / NS) * 0x01010101u;
                const bool chk = ((lf + 1) & 31) <= min(rem, (uint32_t)CH);
                TW(tw0, for (int it = 0; __any_sync(~0u, chk && ld_acq_smem(ctr) != need); it++) {
                    __nanosleep(40);
                    trap_if(it > (1 << 24));
                });
                load_r(m & (NRB - 1));
                if (t < NS && t + CH > CST_SLOT) mbar_wait(bar_pos + 8, 0);
#pragma unroll
                for (int i = 0; i < CH; i++) {
                    const uint32_t d0 = dlane + ((t + i) & (NS - 1)) * 8192;
                    const uint32_t s8[8] = {sw[i][0].x, sw[i][0].y, sw[i][0].z, sw[i][0].w, sw[i][1].x, sw[i][1].y, sw[i][1].z, sw[i][1].w};
                    if (i + 1 < rem) {
#pragma unroll
                        for (int e = 0; e < 16; e++) gather((d0 ^ ((e & 7) << 4)) + e * 128, s8[e >> 1], e & 1);
                    } else {
#pragma unroll
                        for (int e = 0; e < 16; e++) gather_if((d0 ^ ((e & 7) << 4)) + e * 128, s8[e >> 1], e & 1);
                        break;
                    }
                }
                if (t < NS && rem <= CH && t + rem <= NS) {
                    const uint32_t d0 = dlane + (t + rem - 1) * 8192;
#pragma unroll 1
                    for (int e = 1; e < 16; e++)
                        if (*reinterpret_cast<const unsigned short*>(slds + (t + rem - 1) * KB + e * 2) == 0)
                            asm volatile("cp.async.cg.shared.global [%0], [%1], 16, 0;" ::"r"(d0 + e * 128), "l"(ab));
                }
                asm volatile("cp.async.mbarrier.arrive.noinc.shared.b64 [%0];" ::"r"(fbar) : "memory");
                next_chunk();
                m++;
            }
            cp_wait_all();
            STAMP(9);
            TWOUT(0, tw0); TWOUT(1, tw1); TWOUT(2, tw2);
        }
        return;
    }

    bar_named(5, THREADS);
    if (lds32(sb + SM_FLAG)) {
        slow_group(sm, sv, pos, src, dst, w2, wr, out, npg);
        return;
    }

    if (wg == 2) {
        asm volatile("setmaxnreg.dec.sync.aligned.u32 24;");
        return;
    }
    asm volatile("setmaxnreg.inc.sync.aligned.u32 216;");
    {
        const int w = warp & 3, g = lane >> 2, q = lane & 3;
        uint32_t wa[4][4][4];
        uint32_t cy[4][4], cu[4];
#pragma unroll
        for (int i = 0; i < 21; i++) {
            const uint4 x = lds128(sb + SM_CST + ((i == 20 ? 40 + w : (w ? 20 : 0) + i) * 32 + lane) * 16);
            uint32_t* y = i < 16 ? wa[i >> 2][i & 3] : i < 20 ? cy[i - 16] : cu;
            y[0] = x.x; y[1] = x.y; y[2] = x.z; y[3] = x.w;
        }
        mbar_arrive(bar_pos + 8);
        static_assert(sb + SM_RING == 1024, "descriptor constants");
        const uint32_t dr0 = (((sb + SM_RT + wg * NRB * CH * 512) & 0x3FFFF) >> 4) | (16u << 16);
        const uint32_t lflags = __shfl_sync(~0u, lane, lane);
        const uint32_t rt_lane = sb + SM_RT + wg * NRB * CH * 512 + lflags * 16;
        const uint32_t rh_lane = __shfl_sync(~0u, w ? sb + SM_SORT + 32 + w * 32 + q * 8 : sb + SM_ONES, lane);
        const uint32_t rh_step = w ? KB : 0;
        const uint32_t rel_lane = __shfl_sync(~0u, sb + SM_REL + (lane == 31 ? (1 + wg) * 64 : 0) + w, lane);
        const uint32_t ex_w = __shfl_sync(~0u, sb + SM_EX + wg * 1728 + (q - 1) * 288 + (16 * w + g) * 4, lane);
        const uint32_t ex_r = __shfl_sync(~0u, sb + SM_EX + wg * 1728 + (w - 1) * 288 + (16 * q + 2 * g) * 4, lane);
        const uint32_t ocol = __shfl_sync(~0u, blk * 128 + w * 32 + q * 8 + g, lane);
        uint32_t one[4];
#pragma unroll
        for (int i = 0; i < 4; i++) one[i] = __shfl_sync(~0u, g == 2 * i ? 0x3f803f80u : 0u, lane);
        const uint32_t fbar0 = sb + SM_BAR + wg * NRB * 8;
        const uint32_t* svp = reinterpret_cast<const uint32_t*>(sv);
        uint32_t* outp = reinterpret_cast<uint32_t*>(out);
        uint32_t t = 0, tend = 0, m = 0, exo = 0, res = 0, tw0 = 0;
        int n = wg;
        uint32_t A[CH][4], aY[4][2];
        uint2 rh[CH];
        float T[32], U[24], Y[4][8], o[4] = {0.f, 0.f, 0.f, 0.f};
        auto next_node = [&](uint32_t r) {
            t = r & 1023;
            tend = r >> 10;
            if (__builtin_expect(t == tend, 0)) {
                while (n < npg && t == tend) {
                    outp[ocol + n * (G * 128)] = __ldg(svp + (ocol + n * (G * 128)));
                    n += NCW;
                    r = lds32(sb + SM_KST + n * 4);
                    t = r & 1023;
                    tend = r >> 10;
                }
            }
        };
        auto weigh = [&](const float* y, const uint32_t* c, uint32_t* a) {
#pragma unroll
            for (int r = 0; r < 2; r++)
                a[r] = hfma2_bf(pack_bf(y[4 + 2 * r], y[5 + 2 * r]), c[2 + r], hmul2_bf(pack_bf(y[2 * r], y[2 * r + 1]), c[r]));
        };
        auto prep_load = [&]() {
            const uint32_t ra = rt_lane + (m & (NRB - 1)) * (CH * 512), ha = rh_lane + t * rh_step, rem = tend - t;
#pragma unroll
            for (int i = 0; i < CH; i++) {
                {
                    asm volatile("{.reg .pred p; setp.gt.u32 p, %8, %9; mov.b32 %4, 0; mov.b32 %5, 0;\n"
                                 "@p ldmatrix.sync.aligned.m8n8.x4.trans.shared.b16 {%0,%1,%2,%3}, [%6];\n"
                                 "@p ld.shared.v2.u32 {%4,%5}, [%7];}"
                                 : "+r"(A[i][0]), "+r"(A[i][1]), "+r"(A[i][2]), "+r"(A[i][3]), "=r"(rh[i].x), "=r"(rh[i].y)
                                 : "r"(ra + i * 512), "r"(ha + i * KB), "r"(rem), "r"(i) : "memory");
                }
            }
        };
        auto prep_mul = [&]() {
#pragma unroll
            for (int i = 0; i < CH; i++)
                asm volatile("mul.rn.bf16x2 %0, %0, %4; mul.rn.bf16x2 %1, %1, %4; mul.rn.bf16x2 %2, %2, %5; mul.rn.bf16x2 %3, %3, %5;"
                             : "+r"(A[i][0]), "+r"(A[i][1]), "+r"(A[i][2]), "+r"(A[i][3]) : "r"(rh[i].x), "r"(rh[i].y));
        };
        auto wait_chunk = [&]() {
            TW(tw0, mbar_wait(fbar0 + (m & (NRB - 1)) * 8, (m / NRB) & 1));
            asm volatile("fence.proxy.async::generic.acquire.sync_restrict::shared::cluster.cluster;" ::: "memory");
        };
        auto issue_first = [&]() {
            const uint32_t dr = dr0 + (m & (NRB - 1)) * (CH * 32), rem = tend - t;
            auto issue = [&](auto cnt) {
                WG_FENCE();
                kstep_mma<false>(T, U, A[0], (t & (NS - 1)) * 512, dr);
#pragma unroll
                for (int i = 1; i < decltype(cnt)::value; i++)
                    kstep_mma<true>(T, U, A[i], ((t + i) & (NS - 1)) * 512, dr + i * 32);
                WG_COMMIT();
            };
            if (rem == 3) issue(IntT<3>());
            else if (rem >= 4) issue(IntT<4>());
            else if (rem == 2) issue(IntT<2>());
            else issue(IntT<1>());
        };
        auto issue_more = [&]() {
            const uint32_t dr = dr0 + (m & (NRB - 1)) * (CH * 32), rem = tend - t;
#pragma unroll
            for (int i = 0; i < CH; i++) {
                if (i < rem) {
                    WG_FENCE();
                    kstep_mma<true>(T, U, A[i], ((t + i) & (NS - 1)) * 512, dr + i * 32);
                    WG_COMMIT();
                }
            }
        };
        auto retire = [&](uint32_t tc, uint32_t c) {
            const uint32_t tl = lflags == 31 ? m * 4 - 4 : tc + lflags;
            asm volatile("wgmma.wait_group.sync.aligned 0;"
                         : "+r"(A[0][0]), "+r"(A[0][1]), "+r"(A[0][2]), "+r"(A[0][3]), "+r"(A[1][0]), "+r"(A[1][1]),
                           "+r"(A[1][2]), "+r"(A[1][3]), "+r"(A[2][0]), "+r"(A[2][1]), "+r"(A[2][2]), "+r"(A[2][3]),
                           "+r"(A[3][0]), "+r"(A[3][1]), "+r"(A[3][2]), "+r"(A[3][3])::"memory");
            release_if(rel_lane + (tl & (NS - 1)) * 4, tl / NS + 1, ((lflags + 1) & 31) <= c);
        };
        auto sum_prev = [&]() {
#pragma unroll
            for (int mt = 0; mt < 4; mt++) mma1688(o, aY[mt], one[mt]);
        };
        auto tail = [&]() {
#pragma unroll
            for (int mt = 0; mt < 4; mt++) weigh(Y[mt], cy[mt], aY[mt]);
            bar_named(wg + 2, 128);
            uint2 e = make_uint2(0u, 0u);
            if (w) e = lds64(ex_r + exo);
            exo ^= 864;
            o[0] = bf_lo(res) + __uint_as_float(e.x);
            o[2] = bf_hi(res) + __uint_as_float(e.y);
        };
        next_node(lds32(sb + SM_KST + n * 4));
        if (n < npg) {
#pragma unroll
            for (int i = 0; i < 32; i++) Y[i >> 3][i & 7] = 0.f;
#pragma unroll
            for (int i = 0; i < 16; i++) A[i >> 2][i & 3] = 0u;
            wait_chunk();
            prep_load();
            prep_mul();
            STAMP(8);
            issue_first();
            int n1 = -1, n2 = -1;
            while (true) {
                const int nc = n;
                const uint32_t rnext = lds32(sb + SM_KST + (n + NCW) * 4);
                if (n2 >= 0) outp[ocol + n2 * (G * 128)] = pack_bf(o[0], o[2]);
                tail();
                asm volatile("ld.global.nc.u32 %0, [%1];" : "=r"(res) : "l"(svp + (ocol + nc * (G * 128))) : "memory");
                while (__builtin_expect(tend - t > CH, 0)) {
                    t += CH;
                    m++;
                    retire(t - CH, CH);
                    prep_load();
                    prep_mul();
                    wait_chunk();
                    issue_more();
                }
                const uint32_t tc = t, c = tend - t;
                m++;
                n += NCW;
                next_node(rnext);
                retire(tc, c);
                prep_load();
                uint32_t tb[16], aU[3][2];
#pragma unroll
                for (int i = 0; i < 16; i++) tb[i] = pack_bf(T[2 * i], T[2 * i + 1]);
#pragma unroll
                for (int x = 0; x < 3; x++) weigh(U + 8 * x, cu, aU[x]);
#pragma unroll
                for (int i = 0; i < 32; i++) Y[i >> 3][i & 7] = 0.f;
                float u[4] = {0.f, 0.f, 0.f, 0.f};
#pragma unroll
                for (int kk = 0; kk < 4; kk++) {
                    mma1688(o, aY[kk], one[kk]);
#pragma unroll
                    for (int mt = 0; mt < 4; mt++) {
                        mma16816(Y[mt], wa[mt][kk], tb[4 * kk], tb[4 * kk + 2]);
                        mma16816(Y[mt] + 4, wa[mt][kk], tb[4 * kk + 1], tb[4 * kk + 3]);
                    }
                    if (kk < 3) mma1688(u, aU[kk], one[kk + 1]);
                }
                prep_mul();
                asm volatile("{.reg .pred p; setp.ne.u32 p, %3, 0; @p st.shared.f32 [%0], %1; @p st.shared.f32 [%0 + 32], %2;}"
                             ::"r"(ex_w + exo), "f"(u[0]), "f"(u[2]), "r"(lflags & 3) : "memory");
                n2 = n1;
                n1 = nc;
                if (n >= npg) break;
                wait_chunk();
                issue_first();
            }
            if (n2 >= 0) outp[ocol + n2 * (G * 128)] = pack_bf(o[0], o[2]);
            tail();
            sum_prev();
            outp[ocol + n1 * (G * 128)] = pack_bf(o[0], o[2]);
        }
        STAMP(9);
        TWOUT(0, tw0);
    }
}

__global__ void bump_epoch_kernel() { g_epoch = (g_epoch + 1u) % TAGMAX; }

}

extern "C" void kernel_launch(void* const* d_in, const int* in_sizes, int n_in, void* d_out, int out_size) {
    const __nv_bfloat16* sv = (const __nv_bfloat16*)d_in[0];
    const __nv_bfloat16* pos = (const __nv_bfloat16*)d_in[1];
    const int* src = (const int*)d_in[2];
    const int* dst = (const int*)d_in[3];
    const __nv_bfloat16* freqs = (const __nv_bfloat16*)d_in[4];
    const __nv_bfloat16* w1 = (const __nv_bfloat16*)d_in[5];
    const __nv_bfloat16* w2 = (const __nv_bfloat16*)d_in[6];
    const __nv_bfloat16* wr = (const __nv_bfloat16*)d_in[7];
    __nv_bfloat16* out = (__nv_bfloat16*)d_out;
    static int fused = -1;
    if (fused < 0) {
        cudaFuncSetAttribute(painn_kernel<0>, cudaFuncAttributeMaxDynamicSharedMemorySize, SMEM_BYTES);
        cudaFuncSetAttribute(painn_kernel<1>, cudaFuncAttributeMaxDynamicSharedMemorySize, SMEM_BYTES);
        cudaFuncSetAttribute(painn_kernel<2>, cudaFuncAttributeMaxDynamicSharedMemorySize, SMEM_BYTES);
        int dev = 0, sms = 0, occ = 0;
        cudaGetDevice(&dev);
        cudaDeviceGetAttribute(&sms, cudaDevAttrMultiProcessorCount, dev);
        cudaOccupancyMaxActiveBlocksPerMultiprocessor(&occ, painn_kernel<0>, THREADS, SMEM_BYTES);
        fused = occ * sms >= G;
    }
    if (fused) {
        painn_kernel<0><<<G, THREADS, SMEM_BYTES>>>(sv, pos, src, dst, freqs, w1, w2, wr, out);
    } else {
        painn_kernel<1><<<G, THREADS, SMEM_BYTES>>>(sv, pos, src, dst, freqs, w1, w2, wr, out);
        painn_kernel<2><<<G, THREADS, SMEM_BYTES>>>(sv, pos, src, dst, freqs, w1, w2, wr, out);
        bump_epoch_kernel<<<1, 1>>>();
    }
}
```

```cpp
#include <cuda_runtime.h>
#include <cuda_bf16.h>
#include <stdint.h>

namespace {

constexpr int NN = 10000;
constexpr int NE = 640000;
constexpr int G = 132;
constexpr int RT_LO = 0x38C0;
constexpr int RT_HI = 0x40A0;
constexpr int RT_N = RT_HI - RT_LO;
constexpr float D_ACTIVE = 4.90625f;

constexpr int THREADS = 512;
constexpr int CT = 384;
constexpr int ET = 352;
constexpr int EV = 3;
constexpr int EPT = EV * 4 + 2;
constexpr int E_VEC = G * ET * EV * 4;
constexpr int E_TAIL = ((NE - E_VEC) / 2 + G - 1) / G;
static_assert(E_TAIL <= ET, "tail");
constexpr int CB = 80;
constexpr uint32_t TAGMAX = 2047;
constexpr int NPG = (NN + G - 1) / G;
constexpr int NTILE = NN / 16;

constexpr size_t WIN = 1u << 24;
constexpr size_t RT_OFF = 1u << 22;
__device__ uint4 g_arena[(2 * WIN + NN * 256) / 16];
__device__ __forceinline__ unsigned char* arena_base() {
    return reinterpret_cast<unsigned char*>((reinterpret_cast<uint64_t>(g_arena) + WIN - 1) & ~(uint64_t)(WIN - 1));
}
__device__ uint4 g_xrec[G * G * CB / 4];
__device__ uint32_t g_xcnt[G * 160];
__device__ uint32_t g_tflag[160];
__device__ uint32_t g_epoch;

#define STAMP(i)
#define TW(acc, ...) __VA_ARGS__
#define TWOUT(i, v)

struct TrueT { static constexpr bool value = true; };
struct FalseT { static constexpr bool value = false; };
__device__ __forceinline__ float bf16r(float x) { return __bfloat162float(__float2bfloat16_rn(x)); }
__device__ __forceinline__ float bf_lo(uint32_t u) { return __uint_as_float(u << 16); }
__device__ __forceinline__ float bf_hi(uint32_t u) { return __uint_as_float(u & 0xffff0000u); }
__device__ __forceinline__ uint32_t pack_bf(float lo, float hi) {
    uint32_t r;
    asm("cvt.rn.bf16x2.f32 %0, %1, %2;" : "=r"(r) : "f"(hi), "f"(lo));
    return r;
}
__device__ __forceinline__ uint32_t hmul2_bf(uint32_t a, uint32_t b) {
    uint32_t r;
    asm("mul.rn.bf16x2 %0, %1, %2;" : "=r"(r) : "r"(a), "r"(b));
    return r;
}
__device__ __forceinline__ uint32_t hsub2_bf(uint32_t a, uint32_t b) {
    uint32_t r;
    asm("sub.rn.bf16x2 %0, %1, %2;" : "=r"(r) : "r"(a), "r"(b));
    return r;
}
__device__ __forceinline__ uint32_t smem_u32(const void* p) { return (uint32_t)__cvta_generic_to_shared(p); }
__device__ __forceinline__ uint32_t opaque(uint32_t x) {
    asm volatile("" : "+r"(x));
    return x;
}
__device__ __forceinline__ void trap_if(bool c) {
    asm volatile("{.reg .pred p; setp.ne.u32 p, %0, 0; @p trap;}" ::"r"((uint32_t)c));
}
__device__ __forceinline__ void mbar_init(uint32_t bar, int cnt) {
    asm volatile("mbarrier.init.shared.b64 [%0], %1;" ::"r"(bar), "r"(cnt) : "memory");
}
__device__ __forceinline__ void mbar_arrive(uint32_t bar) {
    asm volatile("mbarrier.arrive.shared.b64 _, [%0];" ::"r"(bar) : "memory");
}
__device__ __forceinline__ void mbar_arrive_if(uint32_t bar, bool pred) {
    asm volatile("{.reg .pred p; setp.ne.u32 p, %1, 0; @p mbarrier.arrive.shared.b64 _, [%0];}" ::"r"(bar), "r"((uint32_t)pred) : "memory");
}
__device__ __forceinline__ void release_if(uint32_t a, uint32_t v, bool pred) {
    asm volatile("{.reg .pred p; setp.ne.u32 p, %2, 0; @p st.relaxed.cta.shared.u8 [%0], %1;}" ::"r"(a), "r"(v), "r"((uint32_t)pred) : "memory");
}
__device__ __forceinline__ uint32_t ld_acq_smem(uint32_t a) {
    uint32_t v;
    asm volatile("ld.relaxed.cta.shared.u32 %0, [%1];" : "=r"(v) : "r"(a) : "memory");
    return v;
}
__device__ __forceinline__ void mbar_expect_tx(uint32_t bar, uint32_t bytes) {
    asm volatile("mbarrier.arrive.expect_tx.shared.b64 _, [%0], %1;" ::"r"(bar), "r"(bytes) : "memory");
}
__device__ __forceinline__ uint32_t mbar_test(uint32_t bar, uint32_t parity) {
    uint32_t ok;
    asm volatile("{.reg .pred p; mbarrier.test_wait.parity.shared.b64 p, [%1], %2; selp.u32 %0, 1, 0, p;}"
                 : "=r"(ok) : "r"(bar), "r"(parity) : "memory");
    return ok;
}
__device__ __forceinline__ void mbar_wait(uint32_t bar, uint32_t parity) {
    asm volatile(
        "{.reg .pred p, q; .reg .u32 c;\n"
        "mbarrier.try_wait.parity.shared.b64 p, [%0], %1;\n"
        "@p bra.uni DONE;\n"
        "mov.u32 c, 0;\n"
        "LOOP:\n"
        "mbarrier.try_wait.parity.shared.b64 p, [%0], %1, 0x4000;\n"
        "@p bra.uni DONE;\n"
        "add.u32 c, c, 1;\n"
        "setp.gt.u32 q, c, 0x100000;\n"
        "@q trap;\n"
        "bra.uni LOOP;\n"
        "DONE:}"
        ::"r"(bar), "r"(parity) : "memory");
}
__device__ __forceinline__ void fence_async_smem() { asm volatile("fence.proxy.async.shared::cta;" ::: "memory"); }
__device__ __forceinline__ void bulk_g2s(uint32_t dst, const void* src, uint32_t bytes, uint32_t bar) {
    asm volatile("cp.async.bulk.shared::cluster.global.mbarrier::complete_tx::bytes [%0], [%1], %2, [%3];"
                 ::"r"(dst), "l"(src), "r"(bytes), "r"(bar) : "memory");
}
__device__ __forceinline__ void bulk_s2g(void* dst, uint32_t src, uint32_t bytes) {
    asm volatile("cp.async.bulk.global.shared::cta.bulk_group [%0], [%1], %2;" ::"l"(dst), "r"(src), "r"(bytes) : "memory");
}
__device__ __forceinline__ void cp16(uint32_t dst, const void* src) {
    asm volatile("cp.async.cg.shared.global [%0], [%1], 16;" ::"r"(dst), "l"(src) : "memory");
}
__device__ __forceinline__ void cp_wait_all() { asm volatile("cp.async.wait_all;" ::: "memory"); }
__device__ __forceinline__ void bar_named(int id, int n) { asm volatile("bar.sync %0, %1;" ::"r"(id), "r"(n) : "memory"); }
__device__ __forceinline__ bool bar_named_or(int id, int n, bool v) {
    uint32_t r;
    asm volatile("{.reg .pred p, q; setp.ne.u32 p, %3, 0; bar.red.or.pred q, %1, %2, p; selp.u32 %0, 1, 0, q;}"
                 : "=r"(r) : "r"(id), "r"(n), "r"((uint32_t)v) : "memory");
    return r;
}
__device__ __forceinline__ uint4 ld_cg_volatile(const uint4* p) {
    uint4 v;
    asm volatile("ld.relaxed.gpu.global.v4.u32 {%0,%1,%2,%3}, [%4];" : "=r"(v.x), "=r"(v.y), "=r"(v.z), "=r"(v.w) : "l"(p) : "memory");
    return v;
}
__device__ __forceinline__ uint32_t ld_acq(const uint32_t* p) {
    uint32_t v;
    asm volatile("ld.acquire.gpu.global.u32 %0, [%1];" : "=r"(v) : "l"(p) : "memory");
    return v;
}
__device__ __forceinline__ uint32_t ld_rlx(const uint32_t* p) {
    uint32_t v;
    asm volatile("ld.relaxed.gpu.global.u32 %0, [%1];" : "=r"(v) : "l"(p) : "memory");
    return v;
}
__device__ __forceinline__ void st_rlx(uint32_t* p, uint32_t v) {
    asm volatile("st.relaxed.gpu.global.u32 [%0], %1;" ::"l"(p), "r"(v) : "memory");
}
__device__ __forceinline__ void fence_gpu() { asm volatile("fence.acq_rel.gpu;" ::: "memory"); }
__device__ __forceinline__ void ldsm_x4(uint32_t* r, uint32_t a) {
    asm volatile("ldmatrix.sync.aligned.m8n8.x4.shared.b16 {%0,%1,%2,%3}, [%4];"
                 : "=r"(r[0]), "=r"(r[1]), "=r"(r[2]), "=r"(r[3]) : "r"(a) : "memory");
}
__device__ __forceinline__ void ldsm_x4_t(uint32_t* r, uint32_t a) {
    asm volatile("ldmatrix.sync.aligned.m8n8.x4.trans.shared.b16 {%0,%1,%2,%3}, [%4];"
                 : "=r"(r[0]), "=r"(r[1]), "=r"(r[2]), "=r"(r[3]) : "r"(a) : "memory");
}
__device__ __forceinline__ void stsm_x4(uint32_t a, const uint32_t* r) {
    asm volatile("stmatrix.sync.aligned.m8n8.x4.shared.b16 [%0], {%1,%2,%3,%4};" ::"r"(a), "r"(r[0]), "r"(r[1]), "r"(r[2]), "r"(r[3]) : "memory");
}
__device__ __forceinline__ void mma16816(float* d, const uint32_t* a, uint32_t b0, uint32_t b1) {
    asm("mma.sync.aligned.m16n8k16.row.col.f32.bf16.bf16.f32 {%0,%1,%2,%3},{%4,%5,%6,%7},{%8,%9},{%0,%1,%2,%3};"
                 : "+f"(d[0]), "+f"(d[1]), "+f"(d[2]), "+f"(d[3])
                 : "r"(a[0]), "r"(a[1]), "r"(a[2]), "r"(a[3]), "r"(b0), "r"(b1));
}
__device__ __forceinline__ void mma1688(float* d, const uint32_t* a, uint32_t b) {
    asm("mma.sync.aligned.m16n8k8.row.col.f32.bf16.bf16.f32 {%0,%1,%2,%3},{%4,%5},{%6},{%0,%1,%2,%3};"
        : "+f"(d[0]), "+f"(d[1]), "+f"(d[2]), "+f"(d[3]) : "r"(a[0]), "r"(a[1]), "r"(b));
}
__device__ __forceinline__ uint32_t hfma2_bf(uint32_t a, uint32_t b, uint32_t c) {
    uint32_t r;
    asm("fma.rn.bf16x2 %0, %1, %2, %3;" : "=r"(r) : "r"(a), "r"(b), "r"(c));
    return r;
}
__device__ __forceinline__ uint4 lds128(uint32_t a) {
    uint4 v;
    asm volatile("ld.shared.v4.u32 {%0,%1,%2,%3}, [%4];" : "=r"(v.x), "=r"(v.y), "=r"(v.z), "=r"(v.w) : "r"(a) : "memory");
    return v;
}
__device__ __forceinline__ uint2 lds64(uint32_t a) {
    uint2 v;
    asm volatile("ld.shared.v2.u32 {%0,%1}, [%2];" : "=r"(v.x), "=r"(v.y) : "r"(a) : "memory");
    return v;
}
__device__ __forceinline__ uint32_t lds32(uint32_t a) {
    uint32_t v;
    asm volatile("ld.shared.u32 %0, [%1];" : "=r"(v) : "r"(a) : "memory");
    return v;
}
__device__ __forceinline__ uint32_t lds16(uint32_t a) {
    uint32_t v;
    asm volatile("{.reg .u16 t; ld.shared.u16 t, [%1]; cvt.u32.u16 %0, t;}" : "=r"(v) : "r"(a) : "memory");
    return v;
}
__device__ __forceinline__ uint32_t lds8(uint32_t a) {
    uint32_t v;
    asm volatile("ld.relaxed.cta.shared.u8 %0, [%1];" : "=r"(v) : "r"(a) : "memory");
    return v;
}
__device__ __forceinline__ void sts16(uint32_t a, uint32_t x) {
    asm volatile("{.reg .u16 t; cvt.u16.u32 t, %1; st.shared.u16 [%0], t;}" ::"r"(a), "r"(x) : "memory");
}
__device__ __forceinline__ void sts32(uint32_t a, uint32_t x) {
    asm volatile("st.shared.u32 [%0], %1;" ::"r"(a), "r"(x) : "memory");
}
__device__ __forceinline__ void sts32f(uint32_t a, float x) {
    asm volatile("st.shared.f32 [%0], %1;" ::"r"(a), "f"(x) : "memory");
}
__device__ __forceinline__ uint32_t atoms_inc(uint32_t a) {
    uint32_t v;
    asm volatile("atom.shared.add.u32 %0, [%1], 1;" : "=r"(v) : "r"(a));
    return v;
}
__device__ __forceinline__ uint32_t atoms_inc_if(uint32_t a, bool pred) {
    uint32_t v = 0xffffffffu;
    asm volatile("{.reg .pred p; setp.ne.u32 p, %2, 0; @p atom.shared.add.u32 %0, [%1], 1;}" : "+r"(v) : "r"(a), "r"((uint32_t)pred));
    return v;
}
__device__ __forceinline__ int warp_scan(int v, int lane) {
#pragma unroll
    for (int o = 1; o < 32; o <<= 1) {
        int t = __shfl_up_sync(~0u, v, o);
        if (lane >= o) v += t;
    }
    return v;
}

constexpr int NCW = 2;
constexpr int NS = 16;
constexpr int CH = 4;
constexpr int CAPK = 384;
constexpr int KB = 160;
constexpr int RPT = 19;
constexpr int SVROW = 528;
constexpr int WROW = 144;
constexpr int TPC = (NTILE + G - 1) / G;

constexpr int SM_RING = 0;
constexpr int SM_RT = SM_RING + NS * 8192;
constexpr int SM_EX = SM_RT + 16384;
constexpr int SM_SORT = SM_EX + NCW * 2 * 4 * 288;
constexpr int SM_PDST = SM_SORT + CAPK * KB;
constexpr int SM_GCNT = SM_PDST + NPG * 128;
constexpr int SM_NCNT = SM_GCNT + 160 * 4;
constexpr int SM_KST = SM_NCNT + 128 * 4;
constexpr int SM_FLAG = SM_KST + 104 * 4;
constexpr int SM_ONES = SM_FLAG + 16;
constexpr int SM_REL = SM_ONES + CH * KB;
constexpr int SM_BAR = SM_REL + NS * 4;
constexpr int SMEM_BYTES = SM_PDST + 128 * 128;
static_assert(SM_BAR + (NS + 2) * 8 <= SMEM_BYTES && (SM_BAR - SM_GCNT) / 4 <= 2 * ET, "map");
constexpr int SM_POS = SM_RING;
constexpr int SM_SV = SM_POS + 60160;
constexpr int SM_W = SM_SV + TPC * 16 * SVROW;
constexpr int SM_RAW = SM_W + 2 * 64 * WROW;
constexpr int SM_BINS = SM_SORT;
constexpr int CST_SLOT = 8;
constexpr int SM_CST = SM_RING + CST_SLOT * 8192;
static_assert(SM_CST >= SM_SV && SM_CST + 44 * 512 <= SM_W, "constants");
static_assert(RT_N * 8 <= G * 128 && (SM_ONES - SM_GCNT) / 4 >= ET && SM_RAW + RPT * ET * 4 <= SM_SORT && G * CB * 4 <= CAPK * KB && G == 132 && TPC == 5, "phase 1 map");
static_assert(NPG * 1024 <= NS * 8192, "slow path accumulators live in the ring");
static_assert(NPG <= 96 && SMEM_BYTES <= 232448, "sizes");

#define WG_FENCE() asm volatile("wgmma.fence.sync.aligned;" ::: "memory")
#define WG_COMMIT() asm volatile("wgmma.commit_group.sync.aligned;" ::: "memory")
#define WG_WAIT(n) asm volatile("wgmma.wait_group.sync.aligned %0;" ::"n"(n) : "memory")
#define F8(d, o) "+f"(d[o + 0]), "+f"(d[o + 1]), "+f"(d[o + 2]), "+f"(d[o + 3]), "+f"(d[o + 4]), "+f"(d[o + 5]), "+f"(d[o + 6]), "+f"(d[o + 7])

#define O8(d, o) "=f"(d[o + 0]), "=f"(d[o + 1]), "=f"(d[o + 2]), "=f"(d[o + 3]), "=f"(d[o + 4]), "=f"(d[o + 5]), "=f"(d[o + 6]), "=f"(d[o + 7])
#define KSTEP_ASM(ACC)                                                                                              \
    "{.reg .b64 d, r; .reg .b32 t;\n"                                                                               \
    "or.b32 t, %60, 64; mov.b64 d, {t, 0x40000040};\n"                                                              \
    "wgmma.mma_async.sync.aligned.m64n64k16.f32.bf16.bf16 "                                                         \
    "{%0,%1,%2,%3,%4,%5,%6,%7,%8,%9,%10,%11,%12,%13,%14,%15,%16,%17,%18,%19,%20,%21,%22,%23,%24,%25,%26,%27,%28,"   \
    "%29,%30,%31},{%56,%57,%58,%59},d," ACC ",1,1,1;\n"                                                             \
    "mov.b64 r, {%61, 8}; or.b32 t, %60, 192; mov.b64 d, {t, 0x40000040};\n"                                        \
    "wgmma.mma_async.sync.aligned.m64n16k16.f32.bf16.bf16 {%32,%33,%34,%35,%36,%37,%38,%39},d,r," ACC ",1,1,1,1;\n" \
    "or.b32 t, %60, 320; mov.b64 d, {t, 0x40000040};\n"                                                             \
    "wgmma.mma_async.sync.aligned.m64n16k16.f32.bf16.bf16 {%40,%41,%42,%43,%44,%45,%46,%47},d,r," ACC ",1,1,1,1;\n" \
    "or.b32 t, %60, 448; mov.b64 d, {t, 0x40000040};\n"                                                             \
    "wgmma.mma_async.sync.aligned.m64n16k16.f32.bf16.bf16 {%48,%49,%50,%51,%52,%53,%54,%55},d,r," ACC ",1,1,1,1;}"
template <bool ACC>
__device__ __forceinline__ void kstep_mma(float* T, float* U, const uint32_t* a, uint32_t so) {
    constexpr uint32_t dr0 = ((1024 + SM_RT) >> 4) | (16u << 16);
    if (ACC)
        asm volatile(KSTEP_ASM("1")
                     : F8(T, 0), F8(T, 8), F8(T, 16), F8(T, 24), F8(U, 0), F8(U, 8), F8(U, 16)
                     : "r"(a[0]), "r"(a[1]), "r"(a[2]), "r"(a[3]), "r"(so), "r"(dr0 + (so >> 4)) : "memory");
    else
        asm volatile(KSTEP_ASM("0")
                     : O8(T, 0), O8(T, 8), O8(T, 16), O8(T, 24), O8(U, 0), O8(U, 8), O8(U, 16)
                     : "r"(a[0]), "r"(a[1]), "r"(a[2]), "r"(a[3]), "r"(so), "r"(dr0 + (so >> 4)) : "memory");
}
template <int N> struct IntT { static constexpr int value = N; };

__device__ __forceinline__ void wait_table(uint32_t tag, int lane) {
    for (int it = 0;; it++) {
        bool ok = true;
#pragma unroll
        for (int j = 0; j < 5; j++) {
            const int b = j * 32 + lane;
            if (b < G) ok &= ld_rlx(&g_tflag[b]) == tag;
        }
        if (__all_sync(~0u, ok)) break;
        trap_if(it > (1 << 22));
    }
    fence_gpu();
}

__device__ __forceinline__ void table_tile(unsigned char* sm, int tl, int lane) {
    constexpr uint32_t sb = 1024;
    const int tile = blockIdx.x + tl * G;
    if (tile >= NTILE) return;
    const uint32_t frag = sb + SM_SV + (tl * 16 + (lane & 15)) * SVROW + (lane >> 4) * 16;
    uint32_t a[4][4];
#pragma unroll
    for (int kk = 0; kk < 4; kk++) ldsm_x4(a[kk], frag + kk * 32);
    float acc[8][4];
#pragma unroll
    for (int m = 0; m < 2; m++) {
#pragma unroll
        for (int nt = 0; nt < 8; nt++) acc[nt][0] = acc[nt][1] = acc[nt][2] = acc[nt][3] = 0.f;
        const uint32_t wb = sb + SM_W + m * 64 * WROW + (lane & 15) * WROW + (lane >> 4) * 16;
#pragma unroll
        for (int kk = 0; kk < 4; kk++) {
#pragma unroll
            for (int np = 0; np < 4; np++) {
                uint32_t b[4];
                ldsm_x4_t(b, wb + kk * 16 * WROW + np * 32);
                mma16816(acc[2 * np], a[kk], b[0], b[1]);
                mma16816(acc[2 * np + 1], a[kk], b[2], b[3]);
            }
        }
        if (m == 0) {
#pragma unroll
            for (int nt = 0; nt < 8; nt++) {
                float t[4];
#pragma unroll
                for (int i = 0; i < 4; i++) {
                    const float x = bf16r(acc[nt][i]);
                    t[i] = __fdividef(x, 1.0f + __expf(-x));
                }
                a[nt >> 1][(nt & 1) * 2] = pack_bf(t[0], t[1]);
                a[nt >> 1][(nt & 1) * 2 + 1] = pack_bf(t[2], t[3]);
            }
#pragma unroll
            for (int kk = 0; kk < 4; kk++) stsm_x4(frag + kk * 32, a[kk]);
        }
    }
#pragma unroll
    for (int kk = 0; kk < 4; kk++) {
        const uint32_t ph[4] = {pack_bf(acc[2 * kk][0], acc[2 * kk][1]), pack_bf(acc[2 * kk][2], acc[2 * kk][3]),
                                pack_bf(acc[2 * kk + 1][0], acc[2 * kk + 1][1]), pack_bf(acc[2 * kk + 1][2], acc[2 * kk + 1][3])};
        uint32_t v[3][4];
#pragma unroll
        for (int x = 0; x < 3; x++) ldsm_x4(v[x], frag + 128 + x * 128 + kk * 32);
#pragma unroll
        for (int x = 0; x < 3; x++) {
#pragma unroll
            for (int i = 0; i < 4; i++) v[x][i] = hmul2_bf(v[x][i], ph[i]);
            stsm_x4(frag + 128 + x * 128 + kk * 32, v[x]);
        }
    }
    __syncwarp();
    unsigned char* o = arena_base() + (lane >> 4) * WIN + tile * 4096 + (lane & 15) * 16;
#pragma unroll
    for (int r = 0; r < 16; r++)
        *reinterpret_cast<uint4*>(o + r * 256) = *reinterpret_cast<const uint4*>(sm + SM_SV + (tl * 16 + r) * SVROW + lane * 16);
}

__device__ __forceinline__ bool edge_geom(uint32_t axy, uint32_t az, uint32_t bxy, uint32_t bz, uint32_t& w1, uint32_t& w2) {
    const uint32_t rxy = hsub2_bf(axy, bxy), rz = hsub2_bf(az, bz);
    const uint32_t qxy = hmul2_bf(rxy, rxy), qz = hmul2_bf(rz, rz);
    float q = __uint_as_float(pack_bf(0.f, bf_lo(qxy) + bf_hi(qxy) + bf_lo(qz)));
    q = __uint_as_float(pack_bf(0.f, q + 1e-08f));
    float d, rd;
    asm("sqrt.approx.ftz.f32 %0, %1;" : "=f"(d) : "f"(q));
    const uint32_t du = pack_bf(0.f, d);
    d = __uint_as_float(du);
    asm("rcp.approx.ftz.f32 %0, %1;" : "=f"(rd) : "f"(d));
    w1 = __byte_perm(du, pack_bf(0.f, bf_lo(rxy) * rd), 0x7632);
    w2 = pack_bf(bf_hi(rxy) * rd, bf_lo(rz) * rd);
    return d < D_ACTIVE;
}

__device__ __noinline__ void slow_group(unsigned char* sm, const __nv_bfloat16* sv, const __nv_bfloat16* pos,
                                        const int* src, const int* dst, const __nv_bfloat16* w2,
                                        const __nv_bfloat16* wr, __nv_bfloat16* out, int npg) {
    const int tid = threadIdx.x, lane = tid & 31, grp = blockIdx.x;
    float* acc = reinterpret_cast<float*>(sm);
    for (int i = tid; i < npg * 256; i += CT) acc[i] = 0.f;
    bar_named(1, CT);
    const unsigned short* p16 = reinterpret_cast<const unsigned short*>(pos);
    static_assert(NE % 32 == 0, "");
    for (int e0 = tid - lane; e0 < NE; e0 += CT) {
        const int b = dst[e0 + lane], a = src[e0 + lane];
        uint32_t w1 = 0, w2r = 0;
        bool act = false;
        if (b % G == grp)
            act = edge_geom(p16[3 * a] | (p16[3 * a + 1] << 16), p16[3 * a + 2], p16[3 * b] | (p16[3 * b + 1] << 16),
                            p16[3 * b + 2], w1, w2r);
        for (uint32_t todo = __ballot_sync(~0u, act); todo; todo &= todo - 1) {
            const int l = __ffs(todo) - 1;
            const uint32_t ea = __shfl_sync(~0u, a, l), eb = __shfl_sync(~0u, b, l);
            const uint32_t e1 = __shfl_sync(~0u, w1, l), e2 = __shfl_sync(~0u, w2r, l);
            const unsigned short* row = reinterpret_cast<const unsigned short*>(arena_base()) + (size_t)ea * 128;
            const unsigned short* R = reinterpret_cast<const unsigned short*>(arena_base() + RT_OFF) + ((e1 & 0xffff) - RT_LO + 1) * 16;
            const float rh[3] = {bf_hi(e1), bf_lo(e2), bf_hi(e2)};
            float* o = acc + (eb / G) * 256;
            for (int c = lane; c < 64; c += 32) {
                float ps = 0.f, pr = 0.f, ws = 0.f, wv = 0.f, wvr = 0.f;
                for (int j = 0; j < 64; j++) {
                    const float h = bf_lo(__ldcg(row + j));
                    ps += h * __bfloat162float(w2[j * 192 + c]);
                    pr += h * __bfloat162float(w2[j * 192 + 128 + c]);
                }
                for (int k = 0; k < 16; k++) {
                    const float r = bf_lo(__ldcg(R + k));
                    ws += r * __bfloat162float(wr[k * 192 + c]);
                    wv += r * __bfloat162float(wr[k * 192 + 64 + c]);
                    wvr += r * __bfloat162float(wr[k * 192 + 128 + c]);
                }
                atomicAdd(o + c, ps * ws);
                for (int x = 0; x < 3; x++)
                    atomicAdd(o + 64 + x * 64 + c, bf_lo(__ldcg(row + (x ? WIN / 2 - 64 : 64) + x * 64 + c)) * wv + pr * wvr * rh[x]);
            }
        }
    }
    bar_named(1, CT);
    for (int i = tid; i < npg * 256; i += CT) {
        const size_t o = (size_t)((i >> 8) * G + grp) * 256 + (i & 255);
        out[o] = __float2bfloat16_rn(__bfloat162float(sv[o]) + acc[i]);
    }
}

template <int MODE>
__global__ void __launch_bounds__(THREADS, 1)
painn_kernel(const __nv_bfloat16* __restrict__ sv, const __nv_bfloat16* __restrict__ pos,
             const int* __restrict__ src, const int* __restrict__ dst,
             const __nv_bfloat16* __restrict__ freqs, const __nv_bfloat16* __restrict__ w1,
             const __nv_bfloat16* __restrict__ w2, const __nv_bfloat16* __restrict__ wr,
             __nv_bfloat16* __restrict__ out) {
    extern __shared__ __align__(1024) unsigned char sm[];
    const int tid = threadIdx.x, lane = tid & 31;
    const int warp = __shfl_sync(~0u, tid >> 5, 0), wg = warp >> 2;
    const int blk = blockIdx.x;
    constexpr uint32_t sb = 1024;
    const uint32_t bar_pos = sb + SM_BAR + NS * 8;
    STAMP(0);

    const int npg = (NN - blk + G - 1) / G;
    uint32_t tag;
    bool slow = false;
    if (warp >= 11) {
        const int tw = warp - 11, tt = tid - ET;
        trap_if(smem_u32(sm) != sb);
        if (tid == THREADS - 32) {
            for (int i = 0; i < NS; i++) mbar_init(sb + SM_BAR + i * 8, 32);
            mbar_init(bar_pos, 1);
            mbar_init(bar_pos + 8, NCW * 128);
            if (MODE != 1) {
                fence_async_smem();
                mbar_expect_tx(bar_pos, NN * 6);
                bulk_g2s(sb + SM_POS, pos, NN * 6, bar_pos);
            }
        }
        asm volatile("bar.arrive 6, %0;" ::"n"(THREADS) : "memory");
        tag = ld_rlx(&g_epoch) + 1u;
        if (MODE != 2) {
            const uint32_t f2 = __ldg(reinterpret_cast<const uint32_t*>(freqs) + (tt & 7));
            for (int i = tt; i < 1024; i += 160) {
                const int m = i >> 9, r = (i >> 3) & 63, c = i & 7;
                cp16(sb + SM_W + (m * 64 + r) * WROW + c * 16, m == 0 ? w1 + r * 64 + c * 8 : w2 + r * 192 + 64 + c * 8);
            }
            asm volatile("cp.async.commit_group;" ::: "memory");
            const int tile = blk + tw * G;
            if (tile < NTILE) {
#pragma unroll
                for (int i = 0; i < 16; i++)
                    cp16(sb + SM_SV + (tw * 16 + i) * SVROW + lane * 16, sv + (size_t)(tile * 16 + i) * 256 + lane * 8);
            }
            asm volatile("cp.async.commit_group;" ::: "memory");
            if (blk == G - 1 && tt < 8) reinterpret_cast<uint32_t*>(arena_base() + RT_OFF)[tt] = 0u;
            if (const int i = blk * 128 + tt; tt < 128 && i < RT_N * 8) {
                const float d = __uint_as_float((uint32_t)(RT_LO + (i >> 3)) << 16);
                const float arg = bf16r(__fdividef(bf16r(3.14159265358979f * d), 5.0f));
                const float fc = bf16r(0.5f * bf16r(bf16r(cosf(arg)) + 1.0f));
                float sn[2] = {bf16r(d * bf_lo(f2)), bf16r(d * bf_hi(f2))};
#pragma unroll 1
                for (int k = 0; k < 2; k++) {
                    const float x = sinf(sn[0]);
                    sn[0] = sn[1];
                    sn[1] = x;
                }
                const float r0 = bf16r(__fdividef(bf16r(sn[0]), d)) * fc;
                const float r1 = bf16r(__fdividef(bf16r(sn[1]), d)) * fc;
                reinterpret_cast<uint32_t*>(arena_base() + RT_OFF)[i + 8] = pack_bf(r0, r1);
            }
            STAMP(10);
            asm volatile("cp.async.wait_group 1;" ::: "memory");
            bar_named(2, 160);
            cp_wait_all();
            __syncwarp();
            STAMP(1);
            table_tile(sm, tw, lane);
            STAMP(2);
            fence_gpu();
            bar_named(2, 160);
            if (tid == ET) st_rlx(&g_tflag[blk], tag);
            STAMP(3);
        }
        if (MODE != 1 && wg == 3) {
            const int w = warp & 3, g = lane >> 2, q = lane & 3;
            uint4* cst = reinterpret_cast<uint4*>(sm + SM_CST) + lane;
            auto quad = [&](const uint32_t* x, int koff) {
                const uint32_t a0 = __ldg(x + koff * 96), a1 = __ldg(x + (koff + 1) * 96);
                const uint32_t b0 = __ldg(x + (koff + 8) * 96), b1 = __ldg(x + (koff + 9) * 96);
                return make_uint4(__byte_perm(a0, a1, 0x5410), __byte_perm(a0, a1, 0x7632),
                                  __byte_perm(b0, b1, 0x5410), __byte_perm(b0, b1, 0x7632));
            };
#pragma unroll
            for (int v = 0; v < 2; v++) {
#pragma unroll
                for (int kk = 0; kk < 4; kk++)
                    cst[(v * 20 + w * 4 + kk) * 32] = quad(reinterpret_cast<const uint32_t*>(w2 + v * 128) + w * 8 + g, 16 * kk + 2 * q);
                cst[(v * 20 + 16 + w) * 32] = quad(reinterpret_cast<const uint32_t*>(wr + v * 128) + w * 8 + g, 2 * q);
            }
            const unsigned short* wrp = reinterpret_cast<const unsigned short*>(wr) + 64 + 16 * w + g + 2 * q * 192;
            uint32_t x[4];
#pragma unroll
            for (int i = 0; i < 4; i++) {
                const unsigned short* y = wrp + (i >> 1) * 8 * 192 + (i & 1) * 8;
                x[i] = (uint32_t)__ldg(y) | ((uint32_t)__ldg(y + 192) << 16);
            }
            cst[(40 + w) * 32] = make_uint4(x[0], x[1], x[2], x[3]);
        }
    } else {
    uint32_t es[EPT], ed[EPT];
    bool tail = false;
    if (MODE != 2) {
#pragma unroll
        for (int r = 0; r < EV; r++) {
            const int gi = (blk * EV + r) * ET + tid;
            const int4 d4 = __ldcs(reinterpret_cast<const int4*>(dst) + gi);
            const int4 s4 = __ldcs(reinterpret_cast<const int4*>(src) + gi);
            es[4 * r] = s4.x; es[4 * r + 1] = s4.y; es[4 * r + 2] = s4.z; es[4 * r + 3] = s4.w;
            ed[4 * r] = d4.x; ed[4 * r + 1] = d4.y; ed[4 * r + 2] = d4.z; ed[4 * r + 3] = d4.w;
        }
        const int te = E_VEC / 2 + blk * E_TAIL + tid;
        tail = tid < E_TAIL && te < NE / 2;
        int2 s2 = make_int2(0, 0), d2 = make_int2(0, 0);
        if (tail) {
            d2 = __ldcs(reinterpret_cast<const int2*>(dst) + te);
            s2 = __ldcs(reinterpret_cast<const int2*>(src) + te);
        }
        es[EPT - 2] = s2.x; es[EPT - 1] = s2.y;
        ed[EPT - 2] = d2.x; ed[EPT - 1] = d2.y;
    }
    tag = ld_rlx(&g_epoch) + 1u;
    if (MODE != 1) {
        if (tid >= 160 && tid < 160 + 48) asm volatile("prefetch.global.L2 [%0];" ::"l"(wr + (tid - 160) * 64));
        if (tid >= 224) asm volatile("prefetch.global.L2 [%0];" ::"l"(w2 + ((tid - 224) >> 1) * 192 + (tid & 1) * 128));
    }
    sts32(sb + SM_GCNT + tid * 4, 0u);
    if (const int i = tid + ET; i < (SM_BAR - SM_GCNT) / 4)
        sts32(sb + SM_GCNT + i * 4, i >= (SM_ONES - SM_GCNT) / 4 && i < (SM_REL - SM_GCNT) / 4 ? 0x3f803f80u : 0u);
    bar_named(6, THREADS);
    if (MODE != 2) {
        uint32_t rk[EPT];
#pragma unroll
        for (int i = 0; i < EPT; i++) {
            const uint32_t dl = ed[i] / G;
            ed[i] -= dl * G;
            es[i] |= (dl << 14) | (tag << 21);
            rk[i] = atoms_inc_if(sb + SM_GCNT + ed[i] * 4, i < EPT - 2 || tail);
        }
#pragma unroll
        for (int i = 0; i < EPT; i++)
            if (rk[i] < CB) reinterpret_cast<uint32_t*>(sm + SM_BINS)[ed[i] * CB + rk[i]] = es[i];
        STAMP(2);
        bar_named(1, ET);
        {
            const uint32_t c = lane & 15;
            uint32_t cnt[6];
            uint4 v[6];
#pragma unroll
            for (int j = 0; j < 6; j++) {
                const uint32_t g = (j * 11 + warp) * 2 + (lane >> 4);
                cnt[j] = reinterpret_cast<const uint32_t*>(sm + SM_GCNT)[g];
                v[j] = reinterpret_cast<const uint4*>(sm + SM_BINS)[g * (CB / 4) + c];
            }
            auto put = [&](uint4 x, uint32_t g, uint32_t k, uint32_t n) {
                if (k * 4 >= n) x.x = 0;
                if (k * 4 + 1 >= n) x.y = 0;
                if (k * 4 + 2 >= n) x.z = 0;
                if (k * 4 + 3 >= n) x.w = 0;
                __stcg(&g_xrec[(g * G + blk) * (CB / 4) + k], x);
            };
            bool big = false;
#pragma unroll
            for (int j = 0; j < 6; j++) {
                if ((c & 14) * 4 < cnt[j]) put(v[j], (j * 11 + warp) * 2 + (lane >> 4), c, cnt[j]);
                big |= cnt[j] > 64;
            }
            if (big) {
#pragma unroll 1
                for (int j = 0; j < 6; j++) {
                    const uint32_t g = (j * 11 + warp) * 2 + (lane >> 4);
                    const uint32_t n = reinterpret_cast<const uint32_t*>(sm + SM_GCNT)[g];
                    if (n > 64 && c < CB / 4 - 16) put(reinterpret_cast<const uint4*>(sm + SM_BINS)[g * (CB / 4) + 16 + c], g, 16 + c, n);
                }
            }
            if (tid < 136) st_rlx(&g_xcnt[blk * 160 + tid], reinterpret_cast<const uint32_t*>(sm + SM_GCNT)[tid] | (tag << 21));
        }
        STAMP(3);
        if (MODE != 1) bar_named(1, ET);
    }

    if (MODE != 1) {
        for (int i = tid; i < CAPK * KB / 16; i += ET) reinterpret_cast<uint4*>(sm + SM_SORT)[i] = make_uint4(0, 0, 0, 0);
        mbar_wait(bar_pos, 0);
        for (int i = tid; i < npg * 16; i += ET) {
            const unsigned short* pn = reinterpret_cast<const unsigned short*>(sm + SM_POS) + ((i >> 4) * G + blk) * 3;
            reinterpret_cast<uint2*>(sm + SM_PDST)[i] = make_uint2(pn[0] | (pn[1] << 16), pn[2]);
        }
        bar_named(1, ET);
    }
    if (MODE != 1) {
    STAMP(4);
    uint32_t r0[RPT], w1e[RPT], w2e[RPT], rk[RPT];
    int tot_k = 0;
    uint32_t nrec = 0;
    {
        uint32_t mine = tag << 21;
        for (int it = 0;; it++) {
            if (lane < 12) mine = ld_rlx(&g_xcnt[(warp * 12 + lane) * 160 + blk]);
            if (__all_sync(~0u, (mine >> 21) == tag)) break;
            trap_if(it > (1 << 22));
        }
        STAMP(5);
        mine &= 0x1fffff;
        const uint32_t h = lane >> 4, c = lane & 15;
        const uint4* xr = g_xrec + (blk * G + warp * 12 + h) * (CB / 4) + c;
        uint4 v[6];
        uint32_t cnt[6];
#pragma unroll
        for (int j = 0; j < 6; j++) {
            cnt[j] = __shfl_sync(~0u, mine, 2 * j + h);
            if (c * 4 < cnt[j]) v[j] = ld_cg_volatile(xr + j * 2 * (CB / 4));
        }
        const uint32_t nch = (mine + 3) >> 2, incl = warp_scan(nch, lane);
        const uint32_t total = __shfl_sync(~0u, incl, 31) * 4, base = incl - nch;
        slow = total > RPT * 32 || __any_sync(~0u, mine > CB);
        uint4* raw = reinterpret_cast<uint4*>(sm + SM_RAW) + warp * (RPT * 8);
        auto valid = [&](const uint4& x, uint32_t k, uint32_t n) {
            return (x.x >> 21) == tag && (k * 4 + 1 >= n || (x.y >> 21) == tag) && (k * 4 + 2 >= n || (x.z >> 21) == tag) &&
                   (k * 4 + 3 >= n || (x.w >> 21) == tag);
        };
        for (int it = 0;; it++) {
            bool redo = false;
#pragma unroll
            for (int j = 0; j < 6; j++) {
                if (c * 4 < cnt[j] && !valid(v[j], c, cnt[j])) {
                    v[j] = ld_cg_volatile(xr + j * 2 * (CB / 4));
                    redo = true;
                }
            }
            if (!__any_sync(~0u, redo)) break;
            trap_if(it > (1 << 22));
        }
        STAMP(1);
        if (!slow) {
#pragma unroll
            for (int j = 0; j < 6; j++) {
                const uint32_t o = __shfl_sync(~0u, base, 2 * j + h);
                if (c * 4 < cnt[j]) raw[o + c] = v[j];
            }
            if (__any_sync(~0u, mine > 64)) {
#pragma unroll 1
                for (int j = 0; j < 6; j++) {
                    const uint32_t o = __shfl_sync(~0u, base, 2 * j + h), n = __shfl_sync(~0u, mine, 2 * j + h);
                    if ((16 + c) * 4 < n) {
                        uint4 x;
                        for (int it = 0;; it++) {
                            x = ld_cg_volatile(xr + j * 2 * (CB / 4) + 16);
                            if (valid(x, 16 + c, n)) break;
                            trap_if(it > (1 << 22));
                        }
                        raw[o + 16 + c] = x;
                    }
                }
            }
            __syncwarp();
            auto geom = [&](int i) {
                const uint32_t r = reinterpret_cast<const uint32_t*>(raw)[i * 32 + lane];
                const uint32_t a = min(r & 0x3fff, NN - 1u);
                const uint32_t* pa = reinterpret_cast<const uint32_t*>(sm + SM_POS + ((a * 6) & ~3u));
                const uint32_t a0 = pa[0], a1 = pa[1];
                const uint2 pb = *reinterpret_cast<const uint2*>(sm + SM_PDST + ((r >> 7) & (127 << 7)) + (lane & 15) * 8);
                const bool act = edge_geom(__funnelshift_r(a0, a1, a << 4), __funnelshift_r(a1, 0u, a << 4), pb.x, pb.y, w1e[i], w2e[i]);
                r0[i] = act && (r >> 21) == tag && i * 32 + lane < total ? r & 0x1fffff : 0xffffffffu;
            };
#pragma unroll
            for (int i = 0; i < 14; i++) geom(i);
#pragma unroll
            for (int i = 14; i < RPT; i++) r0[i] = 0xffffffffu;
            if (total > 14 * 32) {
                geom(14);
                geom(15);
                if (total > 16 * 32) {
#pragma unroll
                    for (int i = 16; i < RPT; i++) geom(i);
                }
            }
            nrec = total;
#pragma unroll
            for (int i = 0; i < RPT; i++)
                if (i < 14 || i * 32 < total) rk[i] = atoms_inc(sb + SM_NCNT + min(r0[i] >> 14, 96u + lane) * 4);
        }
    }
    STAMP(6);
    slow = bar_named_or(1, ET, slow);
    if (tag == TAGMAX && !slow)
        for (int i = tid; i < G * CB / 4; i += ET) g_xrec[blk * G * (CB / 4) + i] = make_uint4(0, 0, 0, 0);
    if (!slow) {
        STAMP(10);
        {
            int k[4], s = 0;
#pragma unroll
            for (int j = 0; j < 3; j++) {
                k[j] = s;
                s += max((reinterpret_cast<const uint32_t*>(sm + SM_NCNT)[lane * 3 + j] + 15) >> 4, lane * 3 + j < npg ? 1u : 0u);
            }
            k[3] = s;
            const int incl = warp_scan(s, lane);
            tot_k = __shfl_sync(~0u, incl, 31);
#pragma unroll
            for (int j = 0; j < 3; j++)
                reinterpret_cast<uint32_t*>(sm + SM_KST)[lane * 3 + j] = (incl - s + k[j]) | ((incl - s + k[j + 1]) << 10);
            __syncwarp();
        }
        slow = tot_k > CAPK - CH;
        if (!slow) {
#pragma unroll
            for (int i = 0; i < RPT; i++) {
                if (i < 14 || i * 32 < nrec) {
                    const uint32_t ks = reinterpret_cast<const uint32_t*>(sm + SM_KST)[min(r0[i] >> 14, 96u)] & 1023;
                    const uint32_t e = rk[i] & 15, kb = sb + SM_SORT + (ks + (rk[i] >> 4)) * KB;
                    rk[i] = kb + 8 * ((e & 7) >> 1) + 2 * (e & 1) + 4 * (e >> 3);
                    asm volatile("{.reg .pred p; .reg .u16 a; setp.ne.u32 p, %1, 0xffffffff;\n"
                                 "cvt.u16.u32 a, %2; @p st.shared.u16 [%0], a;\n"
                                 "cvt.u16.u32 a, %3; @p st.shared.u16 [%0 + 32], a;}"
                                 ::"r"(kb + e * 2), "r"(r0[i]), "r"((r0[i] & 0x3fff) + 1), "r"(w1e[i] - (RT_LO - 1)));
                }
            }
        }
    }
    if (tid == 0) sts32(sb + SM_FLAG, slow ? 0 : tot_k);
    asm volatile("bar.arrive 5, %0;" ::"n"(ET + 128) : "memory");
    if (!slow) {
#pragma unroll
        for (int i = 0; i < RPT; i++) {
            if (i < 14 || i * 32 < nrec)
                asm volatile("{.reg .pred p; .reg .u16 a, b; setp.ne.u32 p, %1, 0xffffffff;\n"
                             "mov.b32 {a, b}, %2; @p st.shared.u16 [%0 + 64], b;\n"
                             "mov.b32 {a, b}, %3; @p st.shared.u16 [%0 + 96], a; @p st.shared.u16 [%0 + 128], b;}"
                             ::"r"(rk[i]), "r"(r0[i]), "r"(w1e[i]), "r"(w2e[i]));
        }
    }
    STAMP(7);
    }
    }
    if (MODE == 1) return;

    if (wg == 3) {
        asm volatile("setmaxnreg.dec.sync.aligned.u32 40;");
        wait_table(tag, lane);
        STAMP(4);
        asm volatile("bar.arrive 7, %0;" ::"n"(THREADS) : "memory");
        bar_named(5, ET + 128);
        if (MODE == 0 && blk == 0 && tid == CT) g_epoch = tag % TAGMAX;
        {
            const uint32_t tot = lds32(sb + SM_FLAG);
            const uint64_t ab = reinterpret_cast<uint64_t>(arena_base());
            const uint32_t ahi = (uint32_t)((ab + (lane >> 4) * WIN) >> 32);
            const uint32_t acst = (uint32_t)(ab + (lane >> 4) * WIN) | ((lane & 15) * 16);
            const uint32_t rlo = (uint32_t)(ab + RT_OFF) + (lane & 1) * 16, rhi = (uint32_t)(ab >> 32);
            const uint32_t dlane = __shfl_sync(~0u, sb + SM_RING + (lane >> 3) * 2048 + (lane & 7) * 16, lane);
            const uint32_t rlane = __shfl_sync(~0u, sb + SM_RT + (lane & 1) * 128 + (lane >> 4) * 256 + ((lane >> 1) & 7) * 16, lane);
            const uint32_t zl = __shfl_sync(~0u, tid >> 9, lane);
            const unsigned char* slds = sm + SM_SORT + zl;
            const unsigned char* dlds = sm + SM_SORT + 32 + (lane >> 1) * 2;
            auto gather = [&](uint32_t dst, uint32_t sw, int hi) {
                asm volatile("{.reg .b64 a; mov.b64 a, {%1, %2}; cp.async.cg.shared.global [%0], [a + -256], 16;}"
                             ::"r"(dst), "r"(__byte_perm(sw, acst, hi ? 0x7324 : 0x7104)), "r"(ahi));
            };
            auto gather_if = [&](uint32_t dst, uint32_t sw, int hi) {
                asm volatile("{.reg .b64 a; .reg .pred p; setp.gt.u32 p, %3, %4; mov.b64 a, {%1, %2};\n"
                             "@p cp.async.cg.shared.global [%0], [a + -256], 16;}"
                             ::"r"(dst), "r"(__byte_perm(sw, acst, hi ? 0x7324 : 0x7104)), "r"(ahi), "r"(sw), "r"(hi ? 0xffffu : 0u));
            };
            STAMP(8);
            uint32_t tw0 = 0, tw1 = 0, tw2 = 0;
            for (uint32_t t = warp & 3; t < tot; t += 4) {
                const uint4 sa = *reinterpret_cast<const uint4*>(slds + t * KB);
                const uint4 sc = *reinterpret_cast<const uint4*>(slds + t * KB + 16);
                const uint32_t di = *reinterpret_cast<const unsigned short*>(dlds + t * KB);
                const uint32_t slot = t & (NS - 1), need = (t / NS) * 0x01010101u;
                TW(tw0, for (int it = 0; ld_acq_smem(sb + SM_REL + slot * 4) != need; it++) {
                    __nanosleep(32);
                    trap_if(it > (1 << 24));
                });
                asm volatile("{.reg .b64 a; mov.b64 a, {%1, %2}; cp.async.ca.shared.global [%0], [a], 16;}"
                             ::"r"(rlane + slot * 512), "r"(rlo + di * 32), "r"(rhi));
                const uint32_t d0 = dlane + slot * 8192;
                const uint32_t s8[8] = {sa.x, sa.y, sa.z, sa.w, sc.x, sc.y, sc.z, sc.w};
                if (t < NS) {
                    if (t >= CST_SLOT) mbar_wait(bar_pos + 8, 0);
#pragma unroll
                    for (int e = 0; e < 16; e++)
                        if (!(s8[e >> 1] >> (16 * (e & 1))))
                            asm volatile("cp.async.cg.shared.global [%0], [%1], 16, 0;" ::"r"(d0 + e * 128), "l"(ab));
                }
                if (__any_sync(~0u, sc.w >> 16)) {
#pragma unroll
                    for (int e = 0; e < 16; e++) gather((d0 ^ ((e & 7) << 4)) + e * 128, s8[e >> 1], e & 1);
                } else {
#pragma unroll
                    for (int e = 0; e < 15; e++) gather_if((d0 ^ ((e & 7) << 4)) + e * 128, s8[e >> 1], e & 1);
                }
                asm volatile("cp.async.mbarrier.arrive.noinc.shared.b64 [%0];" ::"r"(sb + SM_BAR + slot * 8) : "memory");
            }
            cp_wait_all();
            STAMP(9);
            TWOUT(0, tw0); TWOUT(1, tw1); TWOUT(2, tw2);
        }
        return;
    }

    bar_named(7, THREADS);
    if (lds32(sb + SM_FLAG) == 0) {
        slow_group(sm, sv, pos, src, dst, w2, wr, out, npg);
        return;
    }

    if (wg == 2) {
        asm volatile("setmaxnreg.dec.sync.aligned.u32 24;");
        return;
    }
    asm volatile("setmaxnreg.inc.sync.aligned.u32 224;");
    {
        const int w = warp & 3, g = lane >> 2, q = lane & 3;
        uint32_t wa[4][4][4];
        uint32_t cy[4][4], cu[4];
#pragma unroll
        for (int i = 0; i < 21; i++) {
            const uint4 x = lds128(sb + SM_CST + ((i == 20 ? 40 + w : (w ? 20 : 0) + i) * 32 + lane) * 16);
            uint32_t* y = i < 16 ? wa[i >> 2][i & 3] : i < 20 ? cy[i - 16] : cu;
            y[0] = x.x; y[1] = x.y; y[2] = x.z; y[3] = x.w;
        }
        mbar_arrive(bar_pos + 8);
        static_assert(sb + SM_RING == 1024, "descriptor constants");
        const uint32_t lflags = __shfl_sync(~0u, lane, lane);
        const uint32_t rt_lane = sb + SM_RT + lflags * 16;
        const uint32_t rh_lane = __shfl_sync(~0u, w ? sb + SM_SORT + 32 + w * 32 + q * 8 : sb + SM_ONES, lane);
        const uint32_t rh_step = w ? KB : 0;
        const uint32_t ex_w = __shfl_sync(~0u, sb + SM_EX + wg * 2304 + q * 288 + (16 * w + g) * 4, lane);
        const uint32_t ex_r = __shfl_sync(~0u, sb + SM_EX + wg * 2304 + w * 288 + (16 * q + 2 * g) * 4, lane);
        uint32_t one[4];
#pragma unroll
        for (int i = 0; i < 4; i++) one[i] = __shfl_sync(~0u, g == 2 * i ? 0x3f803f80u : 0u, lane);
        constexpr int NSTR = NCW * G * 128;
        const uint32_t ocol = (wg * G + blk) * 128 + w * 32 + q * 8 + g;
        const uint32_t* svp = reinterpret_cast<const uint32_t*>(sv) + ocol;
        uint32_t* outp = reinterpret_cast<uint32_t*>(out) + ocol - 2 * NSTR;
        uint32_t t = 0, tend = 0, exo = 0, res = 0, tw0 = 0;
        int n = wg;
        uint32_t A[CH][4], aY[4][2], so[CH];
        uint2 rh[CH];
        float T[32], U[24], Y[4][8], o[4] = {0.f, 0.f, 0.f, 0.f};
        auto weigh = [&](const float* y, const uint32_t* c, uint32_t* a) {
#pragma unroll
            for (int r = 0; r < 2; r++)
                a[r] = hfma2_bf(pack_bf(y[4 + 2 * r], y[5 + 2 * r]), c[2 + r], hmul2_bf(pack_bf(y[2 * r], y[2 * r + 1]), c[r]));
        };
        auto prep_load = [&](uint32_t cnt) {
            const uint32_t ha = rh_lane + t * rh_step;
#pragma unroll
            for (int i = 0; i < CH; i++) so[i] = ((t + i) & (NS - 1)) * 512;
#pragma unroll
            for (int i = 0; i < CH; i++)
                asm volatile("{.reg .pred p; setp.gt.u32 p, %8, %9; mov.b32 %4, 0; mov.b32 %5, 0;\n"
                             "@p ldmatrix.sync.aligned.m8n8.x4.trans.shared.b16 {%0,%1,%2,%3}, [%6];\n"
                             "@p ld.shared.v2.u32 {%4,%5}, [%7];}"
                             : "+r"(A[i][0]), "+r"(A[i][1]), "+r"(A[i][2]), "+r"(A[i][3]), "=r"(rh[i].x), "=r"(rh[i].y)
                             : "r"(rt_lane + so[i]), "r"(ha + i * KB), "r"(cnt), "r"(i) : "memory");
        };
        auto prep_mul = [&]() {
#pragma unroll
            for (int i = 0; i < CH; i++)
                asm volatile("mul.rn.bf16x2 %0, %0, %4; mul.rn.bf16x2 %1, %1, %4; mul.rn.bf16x2 %2, %2, %5; mul.rn.bf16x2 %3, %3, %5;"
                             : "+r"(A[i][0]), "+r"(A[i][1]), "+r"(A[i][2]), "+r"(A[i][3]) : "r"(rh[i].x), "r"(rh[i].y));
        };
        auto lane_ready = [&](uint32_t r) {
            const uint32_t tl = min((r & 1023) + (lflags & 3), (r >> 10) - 1), slot = tl & (NS - 1), lap = tl / NS;
            const uint32_t rel = lds8(sb + SM_REL + slot * 4 + w);
            const uint32_t full = mbar_test(sb + SM_BAR + slot * 8, lap & 1);
            return rel == lap && full;
        };
        auto wait_chunk = [&]() {
            const uint32_t tl = min(t + (lflags & 3), tend - 1), slot = tl & (NS - 1), lap = tl / NS;
            TW(tw0, asm volatile(
                "{.reg .pred p, q; .reg .u32 c, r;\n"
                "mov.u32 c, 0;\n"
                "LOOP:\n"
                "ld.relaxed.cta.shared.u8 r, [%0];\n"
                "mbarrier.try_wait.parity.shared.b64 p, [%1], %3;\n"
                "setp.eq.and.u32 p, r, %2, p;\n"
                "vote.sync.all.pred p, p, 0xffffffff;\n"
                "@p bra.uni DONE;\n"
                "add.u32 c, c, 1;\n"
                "setp.gt.u32 q, c, 0x400000;\n"
                "@q trap;\n"
                "bra.uni LOOP;\n"
                "DONE:}"
                ::"r"(sb + SM_REL + slot * 4 + w), "r"(sb + SM_BAR + slot * 8), "r"(lap), "r"(lap & 1) : "memory"));
            prep_load(tend - t);
            prep_mul();
        };
        auto issue = [&](auto first) {
            const uint32_t rem = tend - t;
            asm volatile("fence.proxy.async::generic.acquire.sync_restrict::shared::cluster.cluster;" ::: "memory");
            WG_FENCE();
            kstep_mma<!decltype(first)::value>(T, U, A[0], so[0]);
            WG_COMMIT();
#pragma unroll
            for (int i = 1; i < CH; i++) {
                if (rem == i) break;
                WG_FENCE();
                kstep_mma<true>(T, U, A[i], so[i]);
                WG_COMMIT();
            }
        };
        auto retire = [&](uint32_t tc, uint32_t c) {
            const uint32_t tl = tc + lflags;
            asm volatile("wgmma.wait_group.sync.aligned 0;"
                         : "+r"(A[0][0]), "+r"(A[0][1]), "+r"(A[0][2]), "+r"(A[0][3]), "+r"(A[1][0]), "+r"(A[1][1]),
                           "+r"(A[1][2]), "+r"(A[1][3]), "+r"(A[2][0]), "+r"(A[2][1]), "+r"(A[2][2]), "+r"(A[2][3]),
                           "+r"(A[3][0]), "+r"(A[3][1]), "+r"(A[3][2]), "+r"(A[3][3])::"memory");
            release_if(sb + SM_REL + (tl & (NS - 1)) * 4 + w, tl / NS + 1, lflags < c);
        };
        uint2 ex = make_uint2(0u, 0u);
        auto fetch_u = [&]() {
            bar_named(wg + 2, 128);
            ex = lds64(ex_r + exo);
            exo ^= 1152;
        };
        auto store = [&](bool pred) {
            asm volatile("{.reg .pred p; setp.ne.u32 p, %2, 0; @p st.global.u32 [%0], %1;}"
                         ::"l"(outp), "r"(pack_bf(o[0] + __uint_as_float(ex.x), o[2] + __uint_as_float(ex.y))), "r"((uint32_t)pred) : "memory");
        };
        auto tail = [&]() {
#pragma unroll
            for (int mt = 0; mt < 4; mt++) weigh(Y[mt], cy[mt], aY[mt]);
            o[0] = bf_lo(res);
            o[2] = bf_hi(res);
        };
        uint32_t rnext = lds32(sb + SM_KST + n * 4);
        t = rnext & 1023;
        tend = rnext >> 10;
        rnext = lds32(sb + SM_KST + (n + NCW) * 4);
#pragma unroll
        for (int i = 0; i < 32; i++) Y[i >> 3][i & 7] = 0.f;
#pragma unroll
        for (int i = 0; i < 16; i++) A[i >> 2][i & 3] = 0u;
        bool ready;
        while (n < npg) {
          wait_chunk();
          do {
            issue(TrueT());
            store(n >= 2 * NCW);
            tail();
            asm volatile("ld.global.u32 %0, [%3];" : "=r"(res), "+f"(o[0]), "+f"(o[2]) : "l"(svp) : "memory");
            if (__builtin_expect(tend - t > CH, 0)) {
                do {
                    t += CH;
                    retire(t - CH, CH);
                    wait_chunk();
                    issue(FalseT());
                } while (tend - t > CH);
            }
            const uint32_t tc = t, c = tend - t;
            n += NCW;
            t = rnext & 1023;
            tend = rnext >> 10;
            retire(tc, c);
            ready = __all_sync(~0u, lane_ready(rnext)) && n < npg;
            fetch_u();
            prep_load(ready ? tend - t : 0u);
            rnext = lds32(sb + SM_KST + (n + NCW) * 4);
            svp += NSTR;
            outp += NSTR;
            uint32_t tb[16], aU[3][2];
#pragma unroll
            for (int i = 0; i < 16; i++) tb[i] = pack_bf(T[2 * i], T[2 * i + 1]);
#pragma unroll
            for (int x = 0; x < 3; x++) weigh(U + 8 * x, cu, aU[x]);
#pragma unroll
            for (int i = 0; i < 32; i++) Y[i >> 3][i & 7] = 0.f;
            float u[4] = {0.f, 0.f, 0.f, 0.f};
#pragma unroll
            for (int kk = 0; kk < 4; kk++) {
                mma1688(o, aY[kk], one[kk]);
#pragma unroll
                for (int mt = 0; mt < 4; mt++) {
                    mma16816(Y[mt], wa[mt][kk], tb[4 * kk], tb[4 * kk + 2]);
                    mma16816(Y[mt] + 4, wa[mt][kk], tb[4 * kk + 1], tb[4 * kk + 3]);
                }
                if (kk < 3) mma1688(u, aU[kk], one[kk + 1]);
            }
            prep_mul();
            sts32f(ex_w + exo, u[0]);
            sts32f(ex_w + exo + 32, u[2]);
          } while (ready);
        }
        store(true);
        outp += NSTR;
        tail();
        fetch_u();
#pragma unroll
        for (int mt = 0; mt < 4; mt++) mma1688(o, aY[mt], one[mt]);
        store(true);
        STAMP(9);
        TWOUT(0, tw0);
    }
}

__global__ void bump_epoch_kernel() { g_epoch = (g_epoch + 1u) % TAGMAX; }

}

extern "C" void kernel_launch(void* const* d_in, const int* in_sizes, int n_in, void* d_out, int out_size) {
    const __nv_bfloat16* sv = (const __nv_bfloat16*)d_in[0];
    const __nv_bfloat16* pos = (const __nv_bfloat16*)d_in[1];
    const int* src = (const int*)d_in[2];
    const int* dst = (const int*)d_in[3];
    const __nv_bfloat16* freqs = (const __nv_bfloat16*)d_in[4];
    const __nv_bfloat16* w1 = (const __nv_bfloat16*)d_in[5];
    const __nv_bfloat16* w2 = (const __nv_bfloat16*)d_in[6];
    const __nv_bfloat16* wr = (const __nv_bfloat16*)d_in[7];
    __nv_bfloat16* out = (__nv_bfloat16*)d_out;
    static int fused = -1;
    if (fused < 0) {
        cudaFuncSetAttribute(painn_kernel<0>, cudaFuncAttributeMaxDynamicSharedMemorySize, SMEM_BYTES);
        cudaFuncSetAttribute(painn_kernel<1>, cudaFuncAttributeMaxDynamicSharedMemorySize, SMEM_BYTES);
        cudaFuncSetAttribute(painn_kernel<2>, cudaFuncAttributeMaxDynamicSharedMemorySize, SMEM_BYTES);
        int dev = 0, sms = 0, occ = 0;
        cudaGetDevice(&dev);
        cudaDeviceGetAttribute(&sms, cudaDevAttrMultiProcessorCount, dev);
        cudaOccupancyMaxActiveBlocksPerMultiprocessor(&occ, painn_kernel<0>, THREADS, SMEM_BYTES);
        fused = occ * sms >= G;
    }
    if (fused) {
        painn_kernel<0><<<G, THREADS, SMEM_BYTES>>>(sv, pos, src, dst, freqs, w1, w2, wr, out);
    } else {
        painn_kernel<1><<<G, THREADS, SMEM_BYTES>>>(sv, pos, src, dst, freqs, w1, w2, wr, out);
        painn_kernel<2><<<G, THREADS, SMEM_BYTES>>>(sv, pos, src, dst, freqs, w1, w2, wr, out);
        bump_epoch_kernel<<<1, 1>>>();
    }
}
```

```cpp
#include <cuda_runtime.h>
#include <cuda_bf16.h>
#include <stdint.h>

namespace {

constexpr int NN = 10000;
constexpr int NE = 640000;
constexpr int G = 132;
constexpr int RT_LO = 0x38C0;
constexpr int RT_HI = 0x40A0;
constexpr int RT_N = RT_HI - RT_LO;
constexpr float D_ACTIVE = 4.90625f;

constexpr int THREADS = 512;
constexpr int CT = 384;
constexpr int ET = 352;
constexpr int EV = 3;
constexpr int EPT = EV * 4 + 2;
constexpr int E_VEC = G * ET * EV * 4;
constexpr int E_TAIL = ((NE - E_VEC) / 2 + G - 1) / G;
static_assert(E_TAIL <= ET, "tail");
constexpr int CB = 80;
constexpr uint32_t TAGMAX = 2047;
constexpr int NPG = (NN + G - 1) / G;
constexpr int NTILE = NN / 16;

constexpr size_t WIN = 1u << 24;
constexpr size_t RT_OFF = 1u << 22;
__device__ uint4 g_arena[(2 * WIN + NN * 256) / 16];
__device__ __forceinline__ unsigned char* arena_base() {
    return reinterpret_cast<unsigned char*>((reinterpret_cast<uint64_t>(g_arena) + WIN - 1) & ~(uint64_t)(WIN - 1));
}
__device__ uint4 g_xrec[G * G * CB / 4];
__device__ uint32_t g_xcnt[G * 160];
constexpr int MAXM = 6, MAXB = 24;
__device__ uint32_t g_kcnt[160];
__device__ uint4 g_mail[G][MAXB * 10 + 2];
__device__ uint32_t g_mflag[160];
__device__ uint32_t g_tflag[160];
__device__ uint32_t g_epoch;

#define STAMP(i)
#define TW(acc, ...) __VA_ARGS__
#define TWOUT(i, v)

struct TrueT { static constexpr bool value = true; };
struct FalseT { static constexpr bool value = false; };
__device__ __forceinline__ float bf16r(float x) { return __bfloat162float(__float2bfloat16_rn(x)); }
__device__ __forceinline__ float bf_lo(uint32_t u) { return __uint_as_float(u << 16); }
__device__ __forceinline__ float bf_hi(uint32_t u) { return __uint_as_float(u & 0xffff0000u); }
__device__ __forceinline__ uint32_t pack_bf(float lo, float hi) {
    uint32_t r;
    asm("cvt.rn.bf16x2.f32 %0, %1, %2;" : "=r"(r) : "f"(hi), "f"(lo));
    return r;
}
__device__ __forceinline__ uint32_t hmul2_bf(uint32_t a, uint32_t b) {
    uint32_t r;
    asm("mul.rn.bf16x2 %0, %1, %2;" : "=r"(r) : "r"(a), "r"(b));
    return r;
}
__device__ __forceinline__ uint32_t hsub2_bf(uint32_t a, uint32_t b) {
    uint32_t r;
    asm("sub.rn.bf16x2 %0, %1, %2;" : "=r"(r) : "r"(a), "r"(b));
    return r;
}
__device__ __forceinline__ uint32_t smem_u32(const void* p) { return (uint32_t)__cvta_generic_to_shared(p); }
__device__ __forceinline__ uint32_t opaque(uint32_t x) {
    asm volatile("" : "+r"(x));
    return x;
}
__device__ __forceinline__ void trap_if(bool c) {
    asm volatile("{.reg .pred p; setp.ne.u32 p, %0, 0; @p trap;}" ::"r"((uint32_t)c));
}
__device__ __forceinline__ void mbar_init(uint32_t bar, int cnt) {
    asm volatile("mbarrier.init.shared.b64 [%0], %1;" ::"r"(bar), "r"(cnt) : "memory");
}
__device__ __forceinline__ void mbar_arrive(uint32_t bar) {
    asm volatile("mbarrier.arrive.shared.b64 _, [%0];" ::"r"(bar) : "memory");
}
__device__ __forceinline__ void mbar_arrive_if(uint32_t bar, bool pred) {
    asm volatile("{.reg .pred p; setp.ne.u32 p, %1, 0; @p mbarrier.arrive.shared.b64 _, [%0];}" ::"r"(bar), "r"((uint32_t)pred) : "memory");
}
__device__ __forceinline__ void release_if(uint32_t a, uint32_t v, bool pred) {
    asm volatile("{.reg .pred p; setp.ne.u32 p, %2, 0; @p st.relaxed.cta.shared.u8 [%0], %1;}" ::"r"(a), "r"(v), "r"((uint32_t)pred) : "memory");
}
__device__ __forceinline__ uint32_t ld_acq_smem(uint32_t a) {
    uint32_t v;
    asm volatile("ld.relaxed.cta.shared.u32 %0, [%1];" : "=r"(v) : "r"(a) : "memory");
    return v;
}
__device__ __forceinline__ void mbar_expect_tx(uint32_t bar, uint32_t bytes) {
    asm volatile("mbarrier.arrive.expect_tx.shared.b64 _, [%0], %1;" ::"r"(bar), "r"(bytes) : "memory");
}
__device__ __forceinline__ uint32_t mbar_test(uint32_t bar, uint32_t parity) {
    uint32_t ok;
    asm volatile("{.reg .pred p; mbarrier.test_wait.parity.shared.b64 p, [%1], %2; selp.u32 %0, 1, 0, p;}"
                 : "=r"(ok) : "r"(bar), "r"(parity) : "memory");
    return ok;
}
__device__ __forceinline__ void mbar_wait(uint32_t bar, uint32_t parity) {
    asm volatile(
        "{.reg .pred p, q; .reg .u32 c;\n"
        "mbarrier.try_wait.parity.shared.b64 p, [%0], %1;\n"
        "@p bra.uni DONE;\n"
        "mov.u32 c, 0;\n"
        "LOOP:\n"
        "mbarrier.try_wait.parity.shared.b64 p, [%0], %1, 0x4000;\n"
        "@p bra.uni DONE;\n"
        "add.u32 c, c, 1;\n"
        "setp.gt.u32 q, c, 0x100000;\n"
        "@q trap;\n"
        "bra.uni LOOP;\n"
        "DONE:}"
        ::"r"(bar), "r"(parity) : "memory");
}
__device__ __forceinline__ void fence_async_smem() { asm volatile("fence.proxy.async.shared::cta;" ::: "memory"); }
__device__ __forceinline__ void bulk_g2s(uint32_t dst, const void* src, uint32_t bytes, uint32_t bar) {
    asm volatile("cp.async.bulk.shared::cluster.global.mbarrier::complete_tx::bytes [%0], [%1], %2, [%3];"
                 ::"r"(dst), "l"(src), "r"(bytes), "r"(bar) : "memory");
}
__device__ __forceinline__ void bulk_s2g(void* dst, uint32_t src, uint32_t bytes) {
    asm volatile("cp.async.bulk.global.shared::cta.bulk_group [%0], [%1], %2;" ::"l"(dst), "r"(src), "r"(bytes) : "memory");
}
__device__ __forceinline__ void cp16(uint32_t dst, const void* src) {
    asm volatile("cp.async.cg.shared.global [%0], [%1], 16;" ::"r"(dst), "l"(src) : "memory");
}
__device__ __forceinline__ void cp_wait_all() { asm volatile("cp.async.wait_all;" ::: "memory"); }
__device__ __forceinline__ void bar_named(int id, int n) { asm volatile("bar.sync %0, %1;" ::"r"(id), "r"(n) : "memory"); }
__device__ __forceinline__ bool bar_named_or(int id, int n, bool v) {
    uint32_t r;
    asm volatile("{.reg .pred p, q; setp.ne.u32 p, %3, 0; bar.red.or.pred q, %1, %2, p; selp.u32 %0, 1, 0, q;}"
                 : "=r"(r) : "r"(id), "r"(n), "r"((uint32_t)v) : "memory");
    return r;
}
__device__ __forceinline__ uint4 ld_cg_volatile(const uint4* p) {
    uint4 v;
    asm volatile("ld.relaxed.gpu.global.v4.u32 {%0,%1,%2,%3}, [%4];" : "=r"(v.x), "=r"(v.y), "=r"(v.z), "=r"(v.w) : "l"(p) : "memory");
    return v;
}
__device__ __forceinline__ uint32_t ld_acq(const uint32_t* p) {
    uint32_t v;
    asm volatile("ld.acquire.gpu.global.u32 %0, [%1];" : "=r"(v) : "l"(p) : "memory");
    return v;
}
__device__ __forceinline__ uint32_t ld_rlx(const uint32_t* p) {
    uint32_t v;
    asm volatile("ld.relaxed.gpu.global.u32 %0, [%1];" : "=r"(v) : "l"(p) : "memory");
    return v;
}
__device__ __forceinline__ void st_rlx(uint32_t* p, uint32_t v) {
    asm volatile("st.relaxed.gpu.global.u32 [%0], %1;" ::"l"(p), "r"(v) : "memory");
}
__device__ __forceinline__ void fence_gpu() { asm volatile("fence.acq_rel.gpu;" ::: "memory"); }
__device__ __forceinline__ void ldsm_x4(uint32_t* r, uint32_t a) {
    asm volatile("ldmatrix.sync.aligned.m8n8.x4.shared.b16 {%0,%1,%2,%3}, [%4];"
                 : "=r"(r[0]), "=r"(r[1]), "=r"(r[2]), "=r"(r[3]) : "r"(a) : "memory");
}
__device__ __forceinline__ void ldsm_x4_t(uint32_t* r, uint32_t a) {
    asm volatile("ldmatrix.sync.aligned.m8n8.x4.trans.shared.b16 {%0,%1,%2,%3}, [%4];"
                 : "=r"(r[0]), "=r"(r[1]), "=r"(r[2]), "=r"(r[3]) : "r"(a) : "memory");
}
__device__ __forceinline__ void stsm_x4(uint32_t a, const uint32_t* r) {
    asm volatile("stmatrix.sync.aligned.m8n8.x4.shared.b16 [%0], {%1,%2,%3,%4};" ::"r"(a), "r"(r[0]), "r"(r[1]), "r"(r[2]), "r"(r[3]) : "memory");
}
__device__ __forceinline__ void mma16816(float* d, const uint32_t* a, uint32_t b0, uint32_t b1) {
    asm("mma.sync.aligned.m16n8k16.row.col.f32.bf16.bf16.f32 {%0,%1,%2,%3},{%4,%5,%6,%7},{%8,%9},{%0,%1,%2,%3};"
                 : "+f"(d[0]), "+f"(d[1]), "+f"(d[2]), "+f"(d[3])
                 : "r"(a[0]), "r"(a[1]), "r"(a[2]), "r"(a[3]), "r"(b0), "r"(b1));
}
__device__ __forceinline__ void mma1688(float* d, const uint32_t* a, uint32_t b) {
    asm("mma.sync.aligned.m16n8k8.row.col.f32.bf16.bf16.f32 {%0,%1,%2,%3},{%4,%5},{%6},{%0,%1,%2,%3};"
        : "+f"(d[0]), "+f"(d[1]), "+f"(d[2]), "+f"(d[3]) : "r"(a[0]), "r"(a[1]), "r"(b));
}
__device__ __forceinline__ uint32_t hfma2_bf(uint32_t a, uint32_t b, uint32_t c) {
    uint32_t r;
    asm("fma.rn.bf16x2 %0, %1, %2, %3;" : "=r"(r) : "r"(a), "r"(b), "r"(c));
    return r;
}
__device__ __forceinline__ uint4 lds128(uint32_t a) {
    uint4 v;
    asm volatile("ld.shared.v4.u32 {%0,%1,%2,%3}, [%4];" : "=r"(v.x), "=r"(v.y), "=r"(v.z), "=r"(v.w) : "r"(a) : "memory");
    return v;
}
__device__ __forceinline__ uint2 lds64(uint32_t a) {
    uint2 v;
    asm volatile("ld.shared.v2.u32 {%0,%1}, [%2];" : "=r"(v.x), "=r"(v.y) : "r"(a) : "memory");
    return v;
}
__device__ __forceinline__ uint32_t lds32(uint32_t a) {
    uint32_t v;
    asm volatile("ld.shared.u32 %0, [%1];" : "=r"(v) : "r"(a) : "memory");
    return v;
}
__device__ __forceinline__ uint32_t lds16(uint32_t a) {
    uint32_t v;
    asm volatile("{.reg .u16 t; ld.shared.u16 t, [%1]; cvt.u32.u16 %0, t;}" : "=r"(v) : "r"(a) : "memory");
    return v;
}
__device__ __forceinline__ uint32_t lds8(uint32_t a) {
    uint32_t v;
    asm volatile("ld.relaxed.cta.shared.u8 %0, [%1];" : "=r"(v) : "r"(a) : "memory");
    return v;
}
__device__ __forceinline__ void sts16(uint32_t a, uint32_t x) {
    asm volatile("{.reg .u16 t; cvt.u16.u32 t, %1; st.shared.u16 [%0], t;}" ::"r"(a), "r"(x) : "memory");
}
__device__ __forceinline__ void sts32(uint32_t a, uint32_t x) {
    asm volatile("st.shared.u32 [%0], %1;" ::"r"(a), "r"(x) : "memory");
}
__device__ __forceinline__ void sts32f(uint32_t a, float x) {
    asm volatile("st.shared.f32 [%0], %1;" ::"r"(a), "f"(x) : "memory");
}
__device__ __forceinline__ uint32_t atoms_inc(uint32_t a) {
    uint32_t v;
    asm volatile("atom.shared.add.u32 %0, [%1], 1;" : "=r"(v) : "r"(a));
    return v;
}
__device__ __forceinline__ uint32_t atoms_inc_if(uint32_t a, bool pred) {
    uint32_t v = 0xffffffffu;
    asm volatile("{.reg .pred p; setp.ne.u32 p, %2, 0; @p atom.shared.add.u32 %0, [%1], 1;}" : "+r"(v) : "r"(a), "r"((uint32_t)pred));
    return v;
}
__device__ __forceinline__ int warp_scan(int v, int lane) {
#pragma unroll
    for (int o = 1; o < 32; o <<= 1) {
        int t = __shfl_up_sync(~0u, v, o);
        if (lane >= o) v += t;
    }
    return v;
}

constexpr int NCW = 2;
constexpr int NS = 16;
constexpr int CH = 4;
constexpr int CAPK = 384;
constexpr int KB = 160;
constexpr int RPT = 19;
constexpr int SVROW = 528;
constexpr int WROW = 144;
constexpr int TPC = (NTILE + G - 1) / G;

constexpr int SM_RING = 0;
constexpr int SM_RT = SM_RING + NS * 8192;
constexpr int SM_EX = SM_RT + 16384;
constexpr int SM_SORT = SM_EX + NCW * 2 * 4 * 288;
constexpr int SM_PDST = SM_SORT + CAPK * KB;
constexpr int SM_GCNT = SM_PDST + NPG * 128;
constexpr int SM_NCNT = SM_GCNT + 160 * 4;
constexpr int SM_KST = SM_NCNT + 128 * 4;
constexpr int SM_FLAG = SM_KST + 104 * 4;
constexpr int SM_ONES = SM_FLAG + 16;
constexpr int SM_BAR = SM_ONES + CH * KB;
constexpr int SM_REL = SM_BAR + 8;
constexpr int SMEM_BYTES = SM_PDST + 128 * 128;
static_assert(SM_BAR % 16 == 0 && SM_BAR + (NS + 2) * 16 <= SMEM_BYTES && CAPK <= 512 && NPG + MAXM + 2 * NCW <= 96 && (SM_BAR - SM_GCNT) / 4 <= 2 * ET, "map");
constexpr int SM_POS = SM_RING;
constexpr int SM_SV = SM_POS + 60160;
constexpr int SM_W = SM_SV + TPC * 16 * SVROW;
constexpr int SM_RAW = SM_W + 2 * 64 * WROW;
constexpr int SM_BINS = SM_SORT;
constexpr int CST_SLOT = 8;
constexpr int SM_CST = SM_RING + CST_SLOT * 8192;
static_assert(SM_CST >= SM_SV && SM_CST + 44 * 512 <= SM_W, "constants");
static_assert(RT_N * 8 <= G * 128 && (SM_ONES - SM_GCNT) / 4 >= ET && SM_RAW + RPT * ET * 4 <= SM_SORT && G * CB * 4 <= CAPK * KB && G == 132 && TPC == 5, "phase 1 map");
static_assert(NPG * 1024 <= NS * 8192, "slow path accumulators live in the ring");
static_assert(NPG <= 96 && SMEM_BYTES <= 232448, "sizes");

#define WG_FENCE() asm volatile("wgmma.fence.sync.aligned;" ::: "memory")
#define WG_COMMIT() asm volatile("wgmma.commit_group.sync.aligned;" ::: "memory")
#define WG_WAIT(n) asm volatile("wgmma.wait_group.sync.aligned %0;" ::"n"(n) : "memory")
#define F8(d, o) "+f"(d[o + 0]), "+f"(d[o + 1]), "+f"(d[o + 2]), "+f"(d[o + 3]), "+f"(d[o + 4]), "+f"(d[o + 5]), "+f"(d[o + 6]), "+f"(d[o + 7])

#define O8(d, o) "=f"(d[o + 0]), "=f"(d[o + 1]), "=f"(d[o + 2]), "=f"(d[o + 3]), "=f"(d[o + 4]), "=f"(d[o + 5]), "=f"(d[o + 6]), "=f"(d[o + 7])
#define KSTEP_ASM(ACC)                                                                                              \
    "{.reg .b64 d, r; .reg .b32 t;\n"                                                                               \
    "or.b32 t, %60, 64; mov.b64 d, {t, 0x40000040};\n"                                                              \
    "wgmma.mma_async.sync.aligned.m64n64k16.f32.bf16.bf16 "                                                         \
    "{%0,%1,%2,%3,%4,%5,%6,%7,%8,%9,%10,%11,%12,%13,%14,%15,%16,%17,%18,%19,%20,%21,%22,%23,%24,%25,%26,%27,%28,"   \
    "%29,%30,%31},{%56,%57,%58,%59},d," ACC ",1,1,1;\n"                                                             \
    "mov.b64 r, {%61, 8}; or.b32 t, %60, 192; mov.b64 d, {t, 0x40000040};\n"                                        \
    "wgmma.mma_async.sync.aligned.m64n16k16.f32.bf16.bf16 {%32,%33,%34,%35,%36,%37,%38,%39},d,r," ACC ",1,1,1,1;\n" \
    "or.b32 t, %60, 320; mov.b64 d, {t, 0x40000040};\n"                                                             \
    "wgmma.mma_async.sync.aligned.m64n16k16.f32.bf16.bf16 {%40,%41,%42,%43,%44,%45,%46,%47},d,r," ACC ",1,1,1,1;\n" \
    "or.b32 t, %60, 448; mov.b64 d, {t, 0x40000040};\n"                                                             \
    "wgmma.mma_async.sync.aligned.m64n16k16.f32.bf16.bf16 {%48,%49,%50,%51,%52,%53,%54,%55},d,r," ACC ",1,1,1,1;}"
template <bool ACC>
__device__ __forceinline__ void kstep_mma(float* T, float* U, const uint32_t* a, uint32_t so) {
    constexpr uint32_t dr0 = ((1024 + SM_RT) >> 4) | (16u << 16);
    if (ACC)
        asm volatile(KSTEP_ASM("1")
                     : F8(T, 0), F8(T, 8), F8(T, 16), F8(T, 24), F8(U, 0), F8(U, 8), F8(U, 16)
                     : "r"(a[0]), "r"(a[1]), "r"(a[2]), "r"(a[3]), "r"(so), "r"(dr0 + (so >> 4)) : "memory");
    else
        asm volatile(KSTEP_ASM("0")
                     : O8(T, 0), O8(T, 8), O8(T, 16), O8(T, 24), O8(U, 0), O8(U, 8), O8(U, 16)
                     : "r"(a[0]), "r"(a[1]), "r"(a[2]), "r"(a[3]), "r"(so), "r"(dr0 + (so >> 4)) : "memory");
}
template <int N> struct IntT { static constexpr int value = N; };

__device__ __forceinline__ void wait_table(uint32_t tag, int lane) {
    for (int it = 0;; it++) {
        bool ok = true;
#pragma unroll
        for (int j = 0; j < 5; j++) {
            const int b = j * 32 + lane;
            if (b < G) ok &= ld_rlx(&g_tflag[b]) == tag;
        }
        if (__all_sync(~0u, ok)) break;
        trap_if(it > (1 << 22));
    }
    fence_gpu();
}

__device__ __forceinline__ void table_tile(unsigned char* sm, int tl, int lane) {
    constexpr uint32_t sb = 1024;
    const int tile = blockIdx.x + tl * G;
    if (tile >= NTILE) return;
    const uint32_t frag = sb + SM_SV + (tl * 16 + (lane & 15)) * SVROW + (lane >> 4) * 16;
    auto put = [&](int x) {
        __syncwarp();
        unsigned char* o = arena_base() + (x >> 1) * WIN + tile * 4096 + (lane >> 3) * 256 + (x & 1) * 128 + (lane & 7) * 16;
        const unsigned char* i = sm + SM_SV + (tl * 16 + (lane >> 3)) * SVROW + x * 128 + (lane & 7) * 16;
#pragma unroll
        for (int r = 0; r < 4; r++) *reinterpret_cast<uint4*>(o + r * 1024) = *reinterpret_cast<const uint4*>(i + r * 4 * SVROW);
    };
    uint32_t a[4][4];
#pragma unroll
    for (int kk = 0; kk < 4; kk++) ldsm_x4(a[kk], frag + kk * 32);
    float acc[8][4];
#pragma unroll
    for (int m = 0; m < 2; m++) {
#pragma unroll
        for (int nt = 0; nt < 8; nt++) acc[nt][0] = acc[nt][1] = acc[nt][2] = acc[nt][3] = 0.f;
        const uint32_t wb = sb + SM_W + m * 64 * WROW + (lane & 15) * WROW + (lane >> 4) * 16;
#pragma unroll
        for (int kk = 0; kk < 4; kk++) {
#pragma unroll
            for (int np = 0; np < 4; np++) {
                uint32_t b[4];
                ldsm_x4_t(b, wb + kk * 16 * WROW + np * 32);
                mma16816(acc[2 * np], a[kk], b[0], b[1]);
                mma16816(acc[2 * np + 1], a[kk], b[2], b[3]);
            }
        }
        if (m == 0) {
#pragma unroll
            for (int nt = 0; nt < 8; nt++) {
                float t[4];
#pragma unroll
                for (int i = 0; i < 4; i++) {
                    const float x = bf16r(acc[nt][i]);
                    t[i] = __fdividef(x, 1.0f + __expf(-x));
                }
                a[nt >> 1][(nt & 1) * 2] = pack_bf(t[0], t[1]);
                a[nt >> 1][(nt & 1) * 2 + 1] = pack_bf(t[2], t[3]);
            }
#pragma unroll
            for (int kk = 0; kk < 4; kk++) stsm_x4(frag + kk * 32, a[kk]);
            put(0);
        }
    }
    uint32_t ph[4][4];
#pragma unroll
    for (int kk = 0; kk < 4; kk++)
#pragma unroll
        for (int i = 0; i < 4; i++) ph[kk][i] = pack_bf(acc[2 * kk + (i >> 1)][2 * (i & 1)], acc[2 * kk + (i >> 1)][2 * (i & 1) + 1]);
#pragma unroll
    for (int x = 1; x < 4; x++) {
        uint32_t v[4][4];
#pragma unroll
        for (int kk = 0; kk < 4; kk++) ldsm_x4(v[kk], frag + x * 128 + kk * 32);
#pragma unroll
        for (int kk = 0; kk < 4; kk++) {
#pragma unroll
            for (int i = 0; i < 4; i++) v[kk][i] = hmul2_bf(v[kk][i], ph[kk][i]);
            stsm_x4(frag + x * 128 + kk * 32, v[kk]);
        }
        put(x);
    }
}

__device__ __forceinline__ bool edge_geom(uint32_t axy, uint32_t az, uint32_t bxy, uint32_t bz, uint32_t& w1, uint32_t& w2) {
    const uint32_t rxy = hsub2_bf(axy, bxy), rz = hsub2_bf(az, bz);
    const uint32_t qxy = hmul2_bf(rxy, rxy), qz = hmul2_bf(rz, rz);
    float q = __uint_as_float(pack_bf(0.f, bf_lo(qxy) + bf_hi(qxy) + bf_lo(qz)));
    q = __uint_as_float(pack_bf(0.f, q + 1e-08f));
    float d, rd;
    asm("sqrt.approx.ftz.f32 %0, %1;" : "=f"(d) : "f"(q));
    const uint32_t du = pack_bf(0.f, d);
    d = __uint_as_float(du);
    asm("rcp.approx.ftz.f32 %0, %1;" : "=f"(rd) : "f"(d));
    w1 = __byte_perm(du, pack_bf(0.f, bf_lo(rxy) * rd), 0x7632);
    w2 = pack_bf(bf_hi(rxy) * rd, bf_lo(rz) * rd);
    return d < D_ACTIVE;
}

__device__ __noinline__ void slow_group(unsigned char* sm, const __nv_bfloat16* sv, const __nv_bfloat16* pos,
                                        const int* src, const int* dst, const __nv_bfloat16* w2,
                                        const __nv_bfloat16* wr, __nv_bfloat16* out, int npg) {
    const int tid = threadIdx.x, lane = tid & 31, grp = blockIdx.x;
    float* acc = reinterpret_cast<float*>(sm);
    for (int i = tid; i < npg * 256; i += CT) acc[i] = 0.f;
    bar_named(1, CT);
    const unsigned short* p16 = reinterpret_cast<const unsigned short*>(pos);
    static_assert(NE % 32 == 0, "");
    for (int e0 = tid - lane; e0 < NE; e0 += CT) {
        const int b = dst[e0 + lane], a = src[e0 + lane];
        uint32_t w1 = 0, w2r = 0;
        bool act = false;
        if (b % G == grp)
            act = edge_geom(p16[3 * a] | (p16[3 * a + 1] << 16), p16[3 * a + 2], p16[3 * b] | (p16[3 * b + 1] << 16),
                            p16[3 * b + 2], w1, w2r);
        for (uint32_t todo = __ballot_sync(~0u, act); todo; todo &= todo - 1) {
            const int l = __ffs(todo) - 1;
            const uint32_t ea = __shfl_sync(~0u, a, l), eb = __shfl_sync(~0u, b, l);
            const uint32_t e1 = __shfl_sync(~0u, w1, l), e2 = __shfl_sync(~0u, w2r, l);
            const unsigned short* row = reinterpret_cast<const unsigned short*>(arena_base()) + (size_t)ea * 128;
            const unsigned short* R = reinterpret_cast<const unsigned short*>(arena_base() + RT_OFF) + ((e1 & 0xffff) - RT_LO + 1) * 16;
            const float rh[3] = {bf_hi(e1), bf_lo(e2), bf_hi(e2)};
            float* o = acc + (eb / G) * 256;
            for (int c = lane; c < 64; c += 32) {
                float ps = 0.f, pr = 0.f, ws = 0.f, wv = 0.f, wvr = 0.f;
                for (int j = 0; j < 64; j++) {
                    const float h = bf_lo(__ldcg(row + j));
                    ps += h * __bfloat162float(w2[j * 192 + c]);
                    pr += h * __bfloat162float(w2[j * 192 + 128 + c]);
                }
                for (int k = 0; k < 16; k++) {
                    const float r = bf_lo(__ldcg(R + k));
                    ws += r * __bfloat162float(wr[k * 192 + c]);
                    wv += r * __bfloat162float(wr[k * 192 + 64 + c]);
                    wvr += r * __bfloat162float(wr[k * 192 + 128 + c]);
                }
                atomicAdd(o + c, ps * ws);
                for (int x = 0; x < 3; x++)
                    atomicAdd(o + 64 + x * 64 + c, bf_lo(__ldcg(row + (x ? WIN / 2 - 64 : 64) + x * 64 + c)) * wv + pr * wvr * rh[x]);
            }
        }
    }
    bar_named(1, CT);
    for (int i = tid; i < npg * 256; i += CT) {
        const size_t o = (size_t)((i >> 8) * G + grp) * 256 + (i & 255);
        out[o] = __float2bfloat16_rn(__bfloat162float(sv[o]) + acc[i]);
    }
}

template <int MODE>
__device__ __forceinline__ void balance(unsigned char* sm, int npg, uint32_t tag, int lane) {
    constexpr uint32_t sb = 1024;
    constexpr int NODE_COST = 2;
    const int blk = blockIdx.x;
    uint32_t* kst = reinterpret_cast<uint32_t*>(sm + SM_KST);
    uint32_t tot = lds32(sb + SM_FLAG), nodes = npg;
    if (MODE == 0) {
        uint32_t key[5];
        for (int it = 0;; it++) {
            bool ok = true;
#pragma unroll
            for (int j = 0; j < 5; j++) {
                key[j] = ~0u;
                if (j * 32 + lane < G) {
                    key[j] = ld_rlx(&g_kcnt[j * 32 + lane]);
                    ok &= (key[j] >> 21) == tag;
                    key[j] = ((key[j] & 511) << 8) | (j * 32 + lane);
                }
            }
            if (__all_sync(~0u, ok)) break;
            __nanosleep(200);
            trap_if(it > (1 << 22));
        }
        auto below = [&](uint32_t x) {
            uint32_t c = 0;
#pragma unroll
            for (int j = 0; j < 5; j++) c += key[j] < x;
            return __reduce_add_sync(~0u, c);
        };
        const uint32_t mine = (tot << 8) | blk, want = G - 1 - below(mine);
        uint32_t other = 0;
#pragma unroll 1
        for (uint32_t bit = 1u << 16; bit; bit >>= 1)
            if (below(other | bit) <= want) other |= bit;
        const uint32_t ok = other >> 8, ob = other & 255;
        if (ok != 0 && mine > other) {
            uint32_t m = 0, t0 = tot;
            while (m < MAXM) {
                const uint32_t s = kst[npg - 1 - m] & 511;
                const uint32_t moved = tot - t0 + m * NODE_COST, c = t0 - s + NODE_COST;
                if (2 * moved + c > tot - ok || tot - s > MAXB || ok + tot - s > CAPK - CH) break;
                t0 = s;
                m++;
            }
#pragma unroll 1
            for (uint32_t i = lane; i < (tot - t0) * 10; i += 32)
                g_mail[ob][2 + i] = reinterpret_cast<const uint4*>(sm + SM_SORT + t0 * KB)[i];
            if (lane < m) reinterpret_cast<uint32_t*>(g_mail[ob])[lane] = kst[npg - m + lane] + (ok - t0) * 513;
            fence_gpu();
            __syncwarp();
            if (lane == 0) st_rlx(&g_mflag[ob], m | ((tot - t0) << 8) | (tag << 21));
            tot = t0;
            nodes -= m;
        } else if (ok != 0) {
            uint32_t v;
            for (int it = 0; ((v = ld_rlx(&g_mflag[blk])) >> 21) != tag; it++) {
                __nanosleep(100);
                trap_if(it > (1 << 22));
            }
            fence_gpu();
            __syncwarp();
            if (lane == 0) g_mflag[blk] = 0;
            const uint32_t m = v & 255, nb = (v >> 8) & 255;
#pragma unroll 1
            for (uint32_t i = lane; i < nb * 10; i += 32)
                reinterpret_cast<uint4*>(sm + SM_SORT + tot * KB)[i] = __ldcg(&g_mail[blk][2 + i]);
            if (lane < m) kst[npg + lane] = __ldcg(reinterpret_cast<const uint32_t*>(g_mail[blk]) + lane);
            tot += nb;
            nodes += m;
        }
    }
    if (lane == 0) {
        sts32(sb + SM_FLAG + 4, tot);
        sts32(sb + SM_FLAG + 8, nodes);
    }
    mbar_arrive(sb + SM_BAR + (NS + 1) * 16);
}

template <int MODE>
__global__ void __launch_bounds__(THREADS, 1)
painn_kernel(const __nv_bfloat16* __restrict__ sv, const __nv_bfloat16* __restrict__ pos,
             const int* __restrict__ src, const int* __restrict__ dst,
             const __nv_bfloat16* __restrict__ freqs, const __nv_bfloat16* __restrict__ w1,
             const __nv_bfloat16* __restrict__ w2, const __nv_bfloat16* __restrict__ wr,
             __nv_bfloat16* __restrict__ out) {
    extern __shared__ __align__(1024) unsigned char sm[];
    const int tid = threadIdx.x, lane = tid & 31;
    const int warp = __shfl_sync(~0u, tid >> 5, 0), wg = warp >> 2;
    const int blk = blockIdx.x;
    constexpr uint32_t sb = 1024;
    constexpr uint32_t bar_cst = sb + SM_BAR + NS * 16, bar_pos = bar_cst + 8, bar_fin = bar_cst + 16;
    STAMP(0);

    const int npg = (NN - blk + G - 1) / G;
    uint32_t tag;
    bool slow = false;
    if (warp >= 11) {
        const int tw = warp - 11, tt = tid - ET;
        trap_if(smem_u32(sm) != sb);
        if (MODE != 1 && warp == 15) {
            if (lane == 0) {
                mbar_init(bar_pos, 1);
                fence_async_smem();
                mbar_expect_tx(bar_pos, NN * 6);
                bulk_g2s(sb + SM_POS, pos, NN * 6, bar_pos);
            }
            asm volatile("bar.arrive 6, %0;" ::"n"(ET + 32) : "memory");
        }
        tag = ld_rlx(&g_epoch) + 1u;
        if (MODE != 2) {
            const uint32_t f2 = __ldg(reinterpret_cast<const uint32_t*>(freqs) + (tt & 7));
            for (int i = tt; i < 1024; i += 160) {
                const int m = i >> 9, r = (i >> 3) & 63, c = i & 7;
                cp16(sb + SM_W + (m * 64 + r) * WROW + c * 16, m == 0 ? w1 + r * 64 + c * 8 : w2 + r * 192 + 64 + c * 8);
            }
            asm volatile("cp.async.commit_group;" ::: "memory");
            const int tile = blk + tw * G;
            if (tile < NTILE) {
#pragma unroll
                for (int i = 0; i < 16; i++)
                    cp16(sb + SM_SV + (tw * 16 + i) * SVROW + lane * 16, sv + (size_t)(tile * 16 + i) * 256 + lane * 8);
            }
            asm volatile("cp.async.commit_group;" ::: "memory");
            if (blk == G - 1 && tt < 8) reinterpret_cast<uint32_t*>(arena_base() + RT_OFF)[tt] = 0u;
            if (const int i = blk * 128 + tt; tt < 128 && i < RT_N * 8) {
                const float d = __uint_as_float((uint32_t)(RT_LO + (i >> 3)) << 16);
                const float arg = bf16r(__fdividef(bf16r(3.14159265358979f * d), 5.0f));
                const float fc = bf16r(0.5f * bf16r(bf16r(cosf(arg)) + 1.0f));
                float sn[2] = {bf16r(d * bf_lo(f2)), bf16r(d * bf_hi(f2))};
#pragma unroll 1
                for (int k = 0; k < 2; k++) {
                    const float x = sinf(sn[0]);
                    sn[0] = sn[1];
                    sn[1] = x;
                }
                const float r0 = bf16r(__fdividef(bf16r(sn[0]), d)) * fc;
                const float r1 = bf16r(__fdividef(bf16r(sn[1]), d)) * fc;
                reinterpret_cast<uint32_t*>(arena_base() + RT_OFF)[i + 8] = pack_bf(r0, r1);
            }
            STAMP(10);
            asm volatile("cp.async.wait_group 1;" ::: "memory");
            bar_named(2, 160);
            cp_wait_all();
            __syncwarp();
            STAMP(1);
            table_tile(sm, tw, lane);
            STAMP(2);
            fence_gpu();
            bar_named(2, 160);
            if (tid == THREADS - 32) st_rlx(&g_tflag[blk], tag);
            STAMP(3);
        }
        if (MODE != 1 && warp == 15) {
            if (lane <= NS + 1) {
                mbar_init(sb + SM_BAR + lane * 16, lane == NS ? NCW * 128 : 32);
                if (lane < NS) sts32(sb + SM_REL + lane * 16, 0);
            }
            wait_table(tag, lane);
        }
        if (MODE != 1 && warp < 15) {
            const int w = tw, g = lane >> 2, q = lane & 3;
            uint4* cst = reinterpret_cast<uint4*>(sm + SM_CST) + lane;
            auto quad = [&](const uint32_t* x, int koff) {
                const uint32_t a0 = __ldg(x + koff * 96), a1 = __ldg(x + (koff + 1) * 96);
                const uint32_t b0 = __ldg(x + (koff + 8) * 96), b1 = __ldg(x + (koff + 9) * 96);
                return make_uint4(__byte_perm(a0, a1, 0x5410), __byte_perm(a0, a1, 0x7632),
                                  __byte_perm(b0, b1, 0x5410), __byte_perm(b0, b1, 0x7632));
            };
#pragma unroll
            for (int v = 0; v < 2; v++) {
#pragma unroll
                for (int kk = 0; kk < 4; kk++)
                    cst[(v * 20 + w * 4 + kk) * 32] = quad(reinterpret_cast<const uint32_t*>(w2 + v * 128) + w * 8 + g, 16 * kk + 2 * q);
                cst[(v * 20 + 16 + w) * 32] = quad(reinterpret_cast<const uint32_t*>(wr + v * 128) + w * 8 + g, 2 * q);
            }
            const unsigned short* wrp = reinterpret_cast<const unsigned short*>(wr) + 64 + 16 * w + g + 2 * q * 192;
            uint32_t x[4];
#pragma unroll
            for (int i = 0; i < 4; i++) {
                const unsigned short* y = wrp + (i >> 1) * 8 * 192 + (i & 1) * 8;
                x[i] = (uint32_t)__ldg(y) | ((uint32_t)__ldg(y + 192) << 16);
            }
            cst[(40 + w) * 32] = make_uint4(x[0], x[1], x[2], x[3]);
        }
    } else {
    uint32_t es[EPT], ed[EPT];
    bool tail = false;
    if (MODE != 2) {
#pragma unroll
        for (int r = 0; r < EV; r++) {
            const int gi = (blk * EV + r) * ET + tid;
            const int4 d4 = __ldcs(reinterpret_cast<const int4*>(dst) + gi);
            const int4 s4 = __ldcs(reinterpret_cast<const int4*>(src) + gi);
            es[4 * r] = s4.x; es[4 * r + 1] = s4.y; es[4 * r + 2] = s4.z; es[4 * r + 3] = s4.w;
            ed[4 * r] = d4.x; ed[4 * r + 1] = d4.y; ed[4 * r + 2] = d4.z; ed[4 * r + 3] = d4.w;
        }
        const int te = E_VEC / 2 + blk * E_TAIL + tid;
        tail = tid < E_TAIL && te < NE / 2;
        int2 s2 = make_int2(0, 0), d2 = make_int2(0, 0);
        if (tail) {
            d2 = __ldcs(reinterpret_cast<const int2*>(dst) + te);
            s2 = __ldcs(reinterpret_cast<const int2*>(src) + te);
        }
        es[EPT - 2] = s2.x; es[EPT - 1] = s2.y;
        ed[EPT - 2] = d2.x; ed[EPT - 1] = d2.y;
    }
    tag = ld_rlx(&g_epoch) + 1u;
    if (MODE != 1) {
        if (tid >= 160 && tid < 160 + 48) asm volatile("prefetch.global.L2 [%0];" ::"l"(wr + (tid - 160) * 64));
        if (tid >= 224) asm volatile("prefetch.global.L2 [%0];" ::"l"(w2 + ((tid - 224) >> 1) * 192 + (tid & 1) * 128));
    }
    sts32(sb + SM_GCNT + tid * 4, 0u);
    if (const int i = tid + ET; i < (SM_BAR - SM_GCNT) / 4)
        sts32(sb + SM_GCNT + i * 4, i >= (SM_ONES - SM_GCNT) / 4 ? 0x3f803f80u : 0u);
    bar_named(1, ET);
    if (MODE != 2) {
        uint32_t rk[EPT];
#pragma unroll
        for (int i = 0; i < EPT; i++) {
            const uint32_t dl = ed[i] / G;
            ed[i] -= dl * G;
            es[i] |= (dl << 14) | (tag << 21);
            rk[i] = atoms_inc_if(sb + SM_GCNT + ed[i] * 4, i < EPT - 2 || tail);
        }
#pragma unroll
        for (int i = 0; i < EPT; i++)
            if (rk[i] < CB) reinterpret_cast<uint32_t*>(sm + SM_BINS)[ed[i] * CB + rk[i]] = es[i];
        STAMP(2);
        bar_named(1, ET);
        {
            const uint32_t c = lane & 15;
            uint32_t cnt[6];
            uint4 v[6];
#pragma unroll
            for (int j = 0; j < 6; j++) {
                const uint32_t g = (j * 11 + warp) * 2 + (lane >> 4);
                cnt[j] = reinterpret_cast<const uint32_t*>(sm + SM_GCNT)[g];
                v[j] = reinterpret_cast<const uint4*>(sm + SM_BINS)[g * (CB / 4) + c];
            }
            auto put = [&](uint4 x, uint32_t g, uint32_t k, uint32_t n) {
                if (k * 4 >= n) x.x = 0;
                if (k * 4 + 1 >= n) x.y = 0;
                if (k * 4 + 2 >= n) x.z = 0;
                if (k * 4 + 3 >= n) x.w = 0;
                __stcg(&g_xrec[(g * G + blk) * (CB / 4) + k], x);
            };
            bool big = false;
#pragma unroll
            for (int j = 0; j < 6; j++) {
                if ((c & 14) * 4 < cnt[j]) put(v[j], (j * 11 + warp) * 2 + (lane >> 4), c, cnt[j]);
                big |= cnt[j] > 64;
            }
            if (big) {
#pragma unroll 1
                for (int j = 0; j < 6; j++) {
                    const uint32_t g = (j * 11 + warp) * 2 + (lane >> 4);
                    const uint32_t n = reinterpret_cast<const uint32_t*>(sm + SM_GCNT)[g];
                    if (n > 64 && c < CB / 4 - 16) put(reinterpret_cast<const uint4*>(sm + SM_BINS)[g * (CB / 4) + 16 + c], g, 16 + c, n);
                }
            }
            if (tid < 136) st_rlx(&g_xcnt[blk * 160 + tid], reinterpret_cast<const uint32_t*>(sm + SM_GCNT)[tid] | (tag << 21));
        }
        STAMP(3);
    }
    if (MODE != 1) bar_named(6, ET + 32);

    if (MODE != 1) {
        for (int i = tid; i < CAPK * KB / 16; i += ET) reinterpret_cast<uint4*>(sm + SM_SORT)[i] = make_uint4(0, 0, 0, 0);
        mbar_wait(bar_pos, 0);
        for (int i = tid; i < npg * 16; i += ET) {
            const unsigned short* pn = reinterpret_cast<const unsigned short*>(sm + SM_POS) + ((i >> 4) * G + blk) * 3;
            reinterpret_cast<uint2*>(sm + SM_PDST)[i] = make_uint2(pn[0] | (pn[1] << 16), pn[2]);
        }
        bar_named(1, ET);
    }
    if (MODE != 1) {
    STAMP(4);
    uint32_t r0[RPT], w1e[RPT], w2e[RPT], rk[RPT];
    int tot_k = 0;
    uint32_t nrec = 0;
    {
        uint32_t mine = tag << 21;
        for (int it = 0;; it++) {
            if (lane < 12) mine = ld_rlx(&g_xcnt[(warp * 12 + lane) * 160 + blk]);
            if (__all_sync(~0u, (mine >> 21) == tag)) break;
            trap_if(it > (1 << 22));
        }
        STAMP(5);
        mine &= 0x1fffff;
        const uint32_t h = lane >> 4, c = lane & 15;
        const uint4* xr = g_xrec + (blk * G + warp * 12 + h) * (CB / 4) + c;
        uint4 v[6];
        uint32_t cnt[6];
#pragma unroll
        for (int j = 0; j < 6; j++) {
            cnt[j] = __shfl_sync(~0u, mine, 2 * j + h);
            if (c * 4 < cnt[j]) v[j] = ld_cg_volatile(xr + j * 2 * (CB / 4));
        }
        const uint32_t nch = (mine + 3) >> 2, incl = warp_scan(nch, lane);
        const uint32_t total = __shfl_sync(~0u, incl, 31) * 4, base = incl - nch;
        slow = total > RPT * 32 || __any_sync(~0u, mine > CB);
        uint4* raw = reinterpret_cast<uint4*>(sm + SM_RAW) + warp * (RPT * 8);
        auto valid = [&](const uint4& x, uint32_t k, uint32_t n) {
            return (x.x >> 21) == tag && (k * 4 + 1 >= n || (x.y >> 21) == tag) && (k * 4 + 2 >= n || (x.z >> 21) == tag) &&
                   (k * 4 + 3 >= n || (x.w >> 21) == tag);
        };
        for (int it = 0;; it++) {
            bool redo = false;
#pragma unroll
            for (int j = 0; j < 6; j++) {
                if (c * 4 < cnt[j] && !valid(v[j], c, cnt[j])) {
                    v[j] = ld_cg_volatile(xr + j * 2 * (CB / 4));
                    redo = true;
                }
            }
            if (!__any_sync(~0u, redo)) break;
            trap_if(it > (1 << 22));
        }
        STAMP(1);
        if (!slow) {
#pragma unroll
            for (int j = 0; j < 6; j++) {
                const uint32_t o = __shfl_sync(~0u, base, 2 * j + h);
                if (c * 4 < cnt[j]) raw[o + c] = v[j];
            }
            if (__any_sync(~0u, mine > 64)) {
#pragma unroll 1
                for (int j = 0; j < 6; j++) {
                    const uint32_t o = __shfl_sync(~0u, base, 2 * j + h), n = __shfl_sync(~0u, mine, 2 * j + h);
                    if ((16 + c) * 4 < n) {
                        uint4 x;
                        for (int it = 0;; it++) {
                            x = ld_cg_volatile(xr + j * 2 * (CB / 4) + 16);
                            if (valid(x, 16 + c, n)) break;
                            trap_if(it > (1 << 22));
                        }
                        raw[o + 16 + c] = x;
                    }
                }
            }
            __syncwarp();
            auto geom = [&](int i) {
                const uint32_t r = reinterpret_cast<const uint32_t*>(raw)[i * 32 + lane];
                const uint32_t a = min(r & 0x3fff, NN - 1u);
                const uint32_t* pa = reinterpret_cast<const uint32_t*>(sm + SM_POS + ((a * 6) & ~3u));
                const uint32_t a0 = pa[0], a1 = pa[1];
                const uint2 pb = *reinterpret_cast<const uint2*>(sm + SM_PDST + ((r >> 7) & (127 << 7)) + (lane & 15) * 8);
                const bool act = edge_geom(__funnelshift_r(a0, a1, a << 4), __funnelshift_r(a1, 0u, a << 4), pb.x, pb.y, w1e[i], w2e[i]);
                r0[i] = act && (r >> 21) == tag && i * 32 + lane < total ? r & 0x1fffff : 0xffffffffu;
            };
#pragma unroll
            for (int i = 0; i < 14; i++) geom(i);
#pragma unroll
            for (int i = 14; i < RPT; i++) r0[i] = 0xffffffffu;
            if (total > 14 * 32) {
                geom(14);
                geom(15);
                if (total > 16 * 32) {
#pragma unroll
                    for (int i = 16; i < RPT; i++) geom(i);
                }
            }
            nrec = total;
#pragma unroll
            for (int i = 0; i < RPT; i++)
                if (i < 14 || i * 32 < total) rk[i] = atoms_inc(sb + SM_NCNT + min(r0[i] >> 14, 96u + lane) * 4);
        }
    }
    STAMP(6);
    slow = bar_named_or(1, ET, slow);
    if (tag == TAGMAX && !slow)
        for (int i = tid; i < G * CB / 4; i += ET) g_xrec[blk * G * (CB / 4) + i] = make_uint4(0, 0, 0, 0);
    if (!slow) {
        STAMP(10);
        {
            int k[4], s = 0;
#pragma unroll
            for (int j = 0; j < 3; j++) {
                k[j] = s;
                s += max((reinterpret_cast<const uint32_t*>(sm + SM_NCNT)[lane * 3 + j] + 15) >> 4, lane * 3 + j < npg ? 1u : 0u);
            }
            k[3] = s;
            const int incl = warp_scan(s, lane);
            tot_k = __shfl_sync(~0u, incl, 31);
#pragma unroll
            for (int j = 0; j < 3; j++)
                reinterpret_cast<uint32_t*>(sm + SM_KST)[lane * 3 + j] =
                    ((incl - s + k[j]) & 511) | (((incl - s + k[j + 1]) & 511) << 9) | (((lane * 3 + j) * G + blk) << 18);
            __syncwarp();
        }
        slow = tot_k > CAPK - CH;
        if (!slow) {
#pragma unroll
            for (int i = 0; i < RPT; i++) {
                if (i < 14 || i * 32 < nrec) {
                    const uint32_t ks = reinterpret_cast<const uint32_t*>(sm + SM_KST)[min(r0[i] >> 14, 96u)] & 511;
                    const uint32_t e = rk[i] & 15, kb = sb + SM_SORT + (ks + (rk[i] >> 4)) * KB;
                    rk[i] = kb + 8 * ((e & 7) >> 1) + 2 * (e & 1) + 4 * (e >> 3);
                    asm volatile("{.reg .pred p; .reg .u16 a; setp.ne.u32 p, %1, 0xffffffff;\n"
                                 "cvt.u16.u32 a, %2; @p st.shared.u16 [%0], a;\n"
                                 "cvt.u16.u32 a, %3; @p st.shared.u16 [%0 + 32], a;}"
                                 ::"r"(kb + e * 2), "r"(r0[i]), "r"((r0[i] & 0x3fff) + 1), "r"(w1e[i] - (RT_LO - 1)));
                }
            }
        }
    }
    if (tid == 0) {
        sts32(sb + SM_FLAG, slow ? 0 : tot_k);
        if (MODE == 0) st_rlx(&g_kcnt[blk], (slow ? 0 : tot_k) | (tag << 21));
    }
    asm volatile("bar.arrive 5, %0;" ::"n"(ET + 128) : "memory");
    if (!slow) {
#pragma unroll
        for (int i = 0; i < RPT; i++) {
            if (i < 14 || i * 32 < nrec)
                asm volatile("{.reg .pred p; .reg .u16 a, b; setp.ne.u32 p, %1, 0xffffffff;\n"
                             "mov.b32 {a, b}, %2; @p st.shared.u16 [%0 + 64], b;\n"
                             "mov.b32 {a, b}, %3; @p st.shared.u16 [%0 + 96], a; @p st.shared.u16 [%0 + 128], b;}"
                             ::"r"(rk[i]), "r"(r0[i]), "r"(w1e[i]), "r"(w2e[i]));
        }
    }
    STAMP(7);
    }
    }
    if (MODE == 1) return;

    if (wg == 3) {
        asm volatile("setmaxnreg.dec.sync.aligned.u32 56;");
        STAMP(4);
        asm volatile("bar.arrive 7, %0;" ::"n"(THREADS) : "memory");
        bar_named(5, ET + 128);
        if (MODE == 0 && blk == 0 && tid == CT) g_epoch = tag % TAGMAX;
        {
            uint32_t tot = lds32(sb + SM_FLAG) ? lds32(sb + SM_KST + (npg - MAXM) * 4) & 511 : 0;
            const uint64_t ab = reinterpret_cast<uint64_t>(arena_base());
            const uint32_t ahi = (uint32_t)((ab + (lane >> 4) * WIN) >> 32);
            const uint32_t acst = (uint32_t)(ab + (lane >> 4) * WIN) | ((lane & 15) * 16);
            const uint32_t rlo = (uint32_t)(ab + RT_OFF) + (lane & 1) * 16, rhi = (uint32_t)(ab >> 32);
            const uint32_t dlane = __shfl_sync(~0u, sb + SM_RING + (lane >> 3) * 2048 + (lane & 7) * 16, lane);
            const uint32_t rlane = __shfl_sync(~0u, sb + SM_RT + (lane & 1) * 128 + (lane >> 4) * 256 + ((lane >> 1) & 7) * 16, lane);
            const uint32_t zl = __shfl_sync(~0u, tid >> 9, lane);
            const unsigned char* slds = sm + SM_SORT + zl;
            const unsigned char* dlds = sm + SM_SORT + 32 + (lane >> 1) * 2;
            auto gather = [&](uint32_t dst, uint32_t sw, int hi) {
                asm volatile("{.reg .b64 a; mov.b64 a, {%1, %2}; cp.async.cg.shared.global [%0], [a + -256], 16;}"
                             ::"r"(dst), "r"(__byte_perm(sw, acst, hi ? 0x7324 : 0x7104)), "r"(ahi));
            };
            auto gather_if = [&](uint32_t dst, uint32_t sw, int hi) {
                asm volatile("{.reg .b64 a; .reg .pred p; setp.gt.u32 p, %3, %4; mov.b64 a, {%1, %2};\n"
                             "@p cp.async.cg.shared.global [%0], [a + -256], 16;}"
                             ::"r"(dst), "r"(__byte_perm(sw, acst, hi ? 0x7324 : 0x7104)), "r"(ahi), "r"(sw), "r"(hi ? 0xffffu : 0u));
            };
            STAMP(8);
            uint32_t tw0 = 0, tw1 = 0, tw2 = 0;
            struct Step { uint4 sa, sc; uint32_t di, rel; };
            auto fetch = [&](Step& x, uint32_t t) {
                x.sa = *reinterpret_cast<const uint4*>(slds + t * KB);
                x.sc = *reinterpret_cast<const uint4*>(slds + t * KB + 16);
                x.di = *reinterpret_cast<const unsigned short*>(dlds + t * KB);
                x.rel = ld_acq_smem(sb + SM_REL + (t & (NS - 1)) * 16 + zl);
            };
            auto run = [&](const Step& x, uint32_t t, auto first, auto&& prefetch) {
                const uint32_t slot = t & (NS - 1), need = (t / NS) * 0x01010101u;
                const uint32_t d0 = dlane + slot * 8192;
                const uint32_t s8[8] = {x.sa.x, x.sa.y, x.sa.z, x.sa.w, x.sc.x, x.sc.y, x.sc.z, x.sc.w};
                if (decltype(first)::value) {
                    if (t >= CST_SLOT) mbar_wait(bar_cst, 0);
#pragma unroll
                    for (int e = 0; e < 16; e++)
                        if (!(s8[e >> 1] >> (16 * (e & 1))))
                            asm volatile("cp.async.cg.shared.global [%0], [%1], 16, 0;" ::"r"(d0 + e * 128), "l"(ab));
                } else if (__any_sync(~0u, x.rel != need)) {
                    TW(tw0, for (int it = 0; ld_acq_smem(sb + SM_REL + slot * 16) != need; it++) {
                        __nanosleep(32);
                        trap_if(it > (1 << 24));
                    });
                }
                prefetch();
                asm volatile("{.reg .b64 a; mov.b64 a, {%1, %2}; cp.async.ca.shared.global [%0], [a], 16;}"
                             ::"r"(rlane + slot * 512), "r"(rlo + x.di * 32), "r"(rhi));
                if (!decltype(first)::value && __any_sync(~0u, x.sc.w >> 16)) {
#pragma unroll
                    for (int e = 0; e < 16; e++) gather((d0 ^ ((e & 7) << 4)) + e * 128, s8[e >> 1], e & 1);
                } else {
#pragma unroll
                    for (int e = 0; e < 16; e++) gather_if((d0 ^ ((e & 7) << 4)) + e * 128, s8[e >> 1], e & 1);
                }
                asm volatile("cp.async.mbarrier.arrive.noinc.shared.b64 [%0];" ::"r"(sb + SM_BAR + slot * 16) : "memory");
            };
            uint32_t t = warp & 3;
            Step x, y;
#pragma unroll 1
            for (; t < min(tot, (uint32_t)NS); t += 4) {
                fetch(x, t);
                run(x, t, TrueT(), [] {});
            }
#pragma unroll 1
            for (int part = 0; part < 2 && tot; part++) {
                fetch(x, t);
#pragma unroll 1
                while (t < tot) {
                    run(x, t, FalseT(), [&] { fetch(y, t + 4); });
                    t += 4;
                    if (t >= tot) break;
                    run(y, t, FalseT(), [&] { fetch(x, t + 4); });
                    t += 4;
                }
                mbar_wait(bar_fin, 0);
                tot = lds32(sb + SM_FLAG + 4);
            }
            cp_wait_all();
            STAMP(9);
            TWOUT(0, tw0); TWOUT(1, tw1); TWOUT(2, tw2);
        }
        return;
    }

    bar_named(7, THREADS);
    if (lds32(sb + SM_FLAG) == 0) {
        slow_group(sm, sv, pos, src, dst, w2, wr, out, npg);
        return;
    }

    if (wg == 2) {
        asm volatile("setmaxnreg.dec.sync.aligned.u32 24;");
        if (warp == 8) balance<MODE>(sm, npg, tag, lane);
        return;
    }
    asm volatile("setmaxnreg.inc.sync.aligned.u32 216;");
    {
        const int w = warp & 3, g = lane >> 2, q = lane & 3;
        uint32_t wa[4][4][4];
        uint32_t cy[4][4], cu[4];
#pragma unroll
        for (int i = 0; i < 21; i++) {
            const uint4 x = lds128(sb + SM_CST + ((i == 20 ? 40 + w : (w ? 20 : 0) + i) * 32 + lane) * 16);
            uint32_t* y = i < 16 ? wa[i >> 2][i & 3] : i < 20 ? cy[i - 16] : cu;
            y[0] = x.x; y[1] = x.y; y[2] = x.z; y[3] = x.w;
        }
        mbar_arrive(bar_cst);
        static_assert(sb + SM_RING == 1024, "descriptor constants");
        const uint32_t l3 = __shfl_sync(~0u, lane & 3, lane);
        const uint32_t rt_lane = __shfl_sync(~0u, sb + SM_RT + lane * 16, lane);
        const uint32_t rh_lane = __shfl_sync(~0u, w ? sb + SM_SORT + 32 + w * 32 + q * 8 : sb + SM_ONES, lane);
        const uint32_t rh_step = w ? KB : 0;
        const uint32_t ex_w = __shfl_sync(~0u, sb + SM_EX + wg * 2304 + q * 288 + (16 * w + g) * 4, lane);
        const uint32_t ex_r = __shfl_sync(~0u, sb + SM_EX + wg * 2304 + w * 288 + (16 * q + 2 * g) * 4, lane);
        uint32_t one[4];
#pragma unroll
        for (int i = 0; i < 4; i++) one[i] = __shfl_sync(~0u, g == 2 * i ? 0x3f803f80u : 0u, lane);
        int id0 = wg * G + blk, d1 = 0, d2 = 0;
        const uint32_t* svp = reinterpret_cast<const uint32_t*>(sv) + id0 * 128 + w * 32 + q * 8 + g;
        uint32_t* outp = reinterpret_cast<uint32_t*>(out) + id0 * 128 + w * 32 + q * 8 + g;
        uint32_t t = 0, tend = 0, exo = 0, res = 0, tw0 = 0;
        int n = wg;
        uint32_t A[CH][4], aY[4][2], so[CH];
        uint2 rh[CH] = {};
        float T[32], U[24], Y[4][8], o[4] = {0.f, 0.f, 0.f, 0.f};
        auto weigh = [&](const float* y, const uint32_t* c, uint32_t* a) {
#pragma unroll
            for (int r = 0; r < 2; r++)
                a[r] = hfma2_bf(pack_bf(y[4 + 2 * r], y[5 + 2 * r]), c[2 + r], hmul2_bf(pack_bf(y[2 * r], y[2 * r + 1]), c[r]));
        };
        auto prep_load = [&]() {
            const uint32_t ha = rh_lane + t * rh_step;
#pragma unroll
            for (int i = 0; i < CH; i++) so[i] = ((t + i) & (NS - 1)) * 512;
#pragma unroll
            for (int i = 0; i < CH - 1; i++)
                asm volatile("{.reg .pred p; setp.gt.u32 p, %8, 2;\n"
                             "@p ldmatrix.sync.aligned.m8n8.x4.trans.shared.b16 {%0,%1,%2,%3}, [%6];\n"
                             "ld.shared.v2.u32 {%4,%5}, [%7];}"
                             : "+r"(A[i][0]), "+r"(A[i][1]), "+r"(A[i][2]), "+r"(A[i][3]), "=r"(rh[i].x), "=r"(rh[i].y)
                             : "r"(rt_lane + so[i]), "r"(ha + i * KB), "r"(i < 2 ? tend - t + 2 : tend - t) : "memory");
            asm volatile("{.reg .pred p; setp.gt.u32 p, %8, 3;\n"
                         "@p ldmatrix.sync.aligned.m8n8.x4.trans.shared.b16 {%0,%1,%2,%3}, [%6];\n"
                         "@p ld.shared.v2.u32 {%4,%5}, [%7];}"
                         : "+r"(A[3][0]), "+r"(A[3][1]), "+r"(A[3][2]), "+r"(A[3][3]), "+r"(rh[3].x), "+r"(rh[3].y)
                         : "r"(rt_lane + so[3]), "r"(ha + 3 * KB), "r"(tend - t) : "memory");
        };
        auto prep_mul = [&]() {
#pragma unroll
            for (int i = 0; i < CH; i++)
                asm volatile("mul.rn.bf16x2 %0, %0, %4; mul.rn.bf16x2 %1, %1, %4; mul.rn.bf16x2 %2, %2, %5; mul.rn.bf16x2 %3, %3, %5;"
                             : "+r"(A[i][0]), "+r"(A[i][1]), "+r"(A[i][2]), "+r"(A[i][3]) : "r"(rh[i].x), "r"(rh[i].y));
        };
        uint32_t slot_addr, slot_lap;
        auto locate = [&]() {
            const uint32_t tl = min(t + l3, tend - 1);
            slot_addr = sb + SM_BAR + (tl & (NS - 1)) * 16;
            slot_lap = tl / NS;
        };
        auto lane_ready = [&]() {
            const uint32_t rel = lds8(slot_addr + 8 + w);
            const uint32_t full = mbar_test(slot_addr, slot_lap & 1);
            return rel == slot_lap && full;
        };
        auto wait_chunk = [&]() {
            TW(tw0, asm volatile(
                "{.reg .pred p, q; .reg .u32 c, r;\n"
                "mov.u32 c, 0;\n"
                "LOOP:\n"
                "ld.relaxed.cta.shared.u8 r, [%0];\n"
                "mbarrier.try_wait.parity.shared.b64 p, [%1], %3;\n"
                "setp.eq.and.u32 p, r, %2, p;\n"
                "vote.sync.all.pred p, p, 0xffffffff;\n"
                "@p bra.uni DONE;\n"
                "add.u32 c, c, 1;\n"
                "setp.gt.u32 q, c, 0x400000;\n"
                "@q trap;\n"
                "bra.uni LOOP;\n"
                "DONE:}"
                ::"r"(slot_addr + 8 + w), "r"(slot_addr), "r"(slot_lap), "r"(slot_lap & 1) : "memory"));
            prep_load();
            prep_mul();
        };
        auto issue = [&](auto first) {
            const uint32_t rem = tend - t;
            asm volatile("fence.proxy.async::generic.acquire.sync_restrict::shared::cluster.cluster;" ::: "memory");
            WG_FENCE();
            kstep_mma<!decltype(first)::value>(T, U, A[0], so[0]);
            WG_COMMIT();
#pragma unroll
            for (int i = 1; i < CH; i++) {
                if (rem == i) break;
                WG_FENCE();
                kstep_mma<true>(T, U, A[i], so[i]);
                WG_COMMIT();
            }
        };
        auto retire = [&]() {
            asm volatile("wgmma.wait_group.sync.aligned 0;"
                         : "+r"(A[0][0]), "+r"(A[0][1]), "+r"(A[0][2]), "+r"(A[0][3]), "+r"(A[1][0]), "+r"(A[1][1]),
                           "+r"(A[1][2]), "+r"(A[1][3]), "+r"(A[2][0]), "+r"(A[2][1]), "+r"(A[2][2]), "+r"(A[2][3]),
                           "+r"(A[3][0]), "+r"(A[3][1]), "+r"(A[3][2]), "+r"(A[3][3])::"memory");
            asm volatile("st.relaxed.cta.shared.u8 [%0], %1;" ::"r"(slot_addr + 8 + w), "r"(slot_lap + 1) : "memory");
        };
        uint2 ex = make_uint2(0u, 0u);
        auto fetch_u = [&]() {
            bar_named(wg + 2, 128);
            ex = lds64(ex_r + exo);
            exo ^= 1152;
        };
        auto store = [&](bool pred) {
            asm volatile("{.reg .pred p; setp.ne.u32 p, %2, 0; @p st.global.u32 [%0], %1;}"
                         ::"l"(outp), "r"(pack_bf(o[0] + __uint_as_float(ex.x), o[2] + __uint_as_float(ex.y))), "r"((uint32_t)pred) : "memory");
        };
        auto tail = [&]() {
#pragma unroll
            for (int mt = 0; mt < 4; mt++) weigh(Y[mt], cy[mt], aY[mt]);
            o[0] = bf_lo(res);
            o[2] = bf_hi(res);
        };
        uint32_t rnext = lds32(sb + SM_KST + n * 4);
        t = rnext & 511;
        tend = (rnext >> 9) & 511;
        rnext = lds32(sb + SM_KST + (n + NCW) * 4);
#pragma unroll
        for (int i = 0; i < 32; i++) Y[i >> 3][i & 7] = 0.f;
#pragma unroll
        for (int i = 0; i < 16; i++) A[i >> 2][i & 3] = 0u;
        bool ready;
        locate();
        int lim = npg - MAXM;
        bool final = false;
        while (true) {
          if (n >= lim) {
              if (final) break;
              mbar_wait(bar_fin, 0);
              lim = lds32(sb + SM_FLAG + 8);
              final = true;
              continue;
          }
          wait_chunk();
          do {
            issue(TrueT());
            store(n >= 2 * NCW);
            tail();
            asm volatile("ld.global.u32 %0, [%3];" : "=r"(res), "+f"(o[0]), "+f"(o[2]) : "l"(svp) : "memory");
            if (__builtin_expect(tend - t > CH, 0)) {
                do {
                    t += CH;
                    retire();
                    locate();
                    wait_chunk();
                    issue(FalseT());
                } while (tend - t > CH);
            }
            n += NCW;
            t = rnext & 511;
            tend = (rnext >> 9) & 511;
            outp += d2;
            d2 = d1;
            d1 = ((int)(rnext >> 18) - id0) * 128;
            id0 = rnext >> 18;
            svp += d1;
            retire();
            locate();
            ready = __all_sync(~0u, lane_ready()) && n < lim;
            prep_load();
            rnext = lds32(sb + SM_KST + (n + NCW) * 4);
            fetch_u();
            uint32_t tb[16], aU[3][2];
#pragma unroll
            for (int i = 0; i < 16; i++) tb[i] = pack_bf(T[2 * i], T[2 * i + 1]);
#pragma unroll
            for (int x = 0; x < 3; x++) weigh(U + 8 * x, cu, aU[x]);
#pragma unroll
            for (int i = 0; i < 32; i++) Y[i >> 3][i & 7] = 0.f;
            float u[4] = {0.f, 0.f, 0.f, 0.f};
#pragma unroll
            for (int kk = 0; kk < 4; kk++) {
                mma1688(o, aY[kk], one[kk]);
#pragma unroll
                for (int mt = 0; mt < 4; mt++) {
                    mma16816(Y[mt], wa[mt][kk], tb[4 * kk], tb[4 * kk + 2]);
                    mma16816(Y[mt] + 4, wa[mt][kk], tb[4 * kk + 1], tb[4 * kk + 3]);
                }
                if (kk < 3) mma1688(u, aU[kk], one[kk + 1]);
            }
            prep_mul();
            sts32f(ex_w + exo, u[0]);
            sts32f(ex_w + exo + 32, u[2]);
          } while (ready);
        }
        store(true);
        outp += d2;
        tail();
        fetch_u();
#pragma unroll
        for (int mt = 0; mt < 4; mt++) mma1688(o, aY[mt], one[mt]);
        store(true);
        STAMP(9);
        TWOUT(0, tw0);
    }
}

__global__ void bump_epoch_kernel() { g_epoch = (g_epoch + 1u) % TAGMAX; }

}

extern "C" void kernel_launch(void* const* d_in, const int* in_sizes, int n_in, void* d_out, int out_size) {
    const __nv_bfloat16* sv = (const __nv_bfloat16*)d_in[0];
    const __nv_bfloat16* pos = (const __nv_bfloat16*)d_in[1];
    const int* src = (const int*)d_in[2];
    const int* dst = (const int*)d_in[3];
    const __nv_bfloat16* freqs = (const __nv_bfloat16*)d_in[4];
    const __nv_bfloat16* w1 = (const __nv_bfloat16*)d_in[5];
    const __nv_bfloat16* w2 = (const __nv_bfloat16*)d_in[6];
    const __nv_bfloat16* wr = (const __nv_bfloat16*)d_in[7];
    __nv_bfloat16* out = (__nv_bfloat16*)d_out;
    static int fused = -1;
    if (fused < 0) {
        cudaFuncSetAttribute(painn_kernel<0>, cudaFuncAttributeMaxDynamicSharedMemorySize, SMEM_BYTES);
        cudaFuncSetAttribute(painn_kernel<1>, cudaFuncAttributeMaxDynamicSharedMemorySize, SMEM_BYTES);
        cudaFuncSetAttribute(painn_kernel<2>, cudaFuncAttributeMaxDynamicSharedMemorySize, SMEM_BYTES);
        int dev = 0, sms = 0, occ = 0;
        cudaGetDevice(&dev);
        cudaDeviceGetAttribute(&sms, cudaDevAttrMultiProcessorCount, dev);
        cudaOccupancyMaxActiveBlocksPerMultiprocessor(&occ, painn_kernel<0>, THREADS, SMEM_BYTES);
        fused = occ * sms >= G;
    }
    if (fused) {
        painn_kernel<0><<<G, THREADS, SMEM_BYTES>>>(sv, pos, src, dst, freqs, w1, w2, wr, out);
    } else {
        painn_kernel<1><<<G, THREADS, SMEM_BYTES>>>(sv, pos, src, dst, freqs, w1, w2, wr, out);
        painn_kernel<2><<<G, THREADS, SMEM_BYTES>>>(sv, pos, src, dst, freqs, w1, w2, wr, out);
        bump_epoch_kernel<<<1, 1>>>();
    }
}
```

```cpp
#include <cuda_runtime.h>
#include <cuda_bf16.h>
#include <stdint.h>

namespace {

constexpr int NN = 10000;
constexpr int NE = 640000;
constexpr int G = 132;
constexpr int RT_LO = 0x38C0;
constexpr int RT_HI = 0x40A0;
constexpr int RT_N = RT_HI - RT_LO;
constexpr float D_ACTIVE = 4.90625f;

constexpr int THREADS = 512;
constexpr int CT = 384;
constexpr int ET = 352;
constexpr int EV = 3;
constexpr int EPT = EV * 4 + 2;
constexpr int E_VEC = G * ET * EV * 4;
constexpr int E_TAIL = ((NE - E_VEC) / 2 + G - 1) / G;
static_assert(E_TAIL <= ET, "tail");
constexpr int CB = 80;
constexpr uint32_t TAGMAX = 2047;
constexpr int NPG = (NN + G - 1) / G;
constexpr int NTILE = NN / 16;

constexpr size_t WIN = 1u << 24;
constexpr size_t RT_OFF = 1u << 22;
__device__ uint4 g_arena[(2 * WIN + NN * 256) / 16];
__device__ __forceinline__ unsigned char* arena_base() {
    return reinterpret_cast<unsigned char*>((reinterpret_cast<uint64_t>(g_arena) + WIN - 1) & ~(uint64_t)(WIN - 1));
}
__device__ uint4 g_xrec[G * G * CB / 4];
__device__ uint32_t g_xcnt[G * 160];
constexpr int MAXM = 6, MAXB = 24;
__device__ uint32_t g_kcnt[160];
__device__ uint4 g_mail[G][MAXB * 10 + 2];
__device__ uint32_t g_mflag[160];
__device__ uint32_t g_tflag[160];
__device__ uint32_t g_epoch;

#define STAMP(i)
#define TW(acc, ...) __VA_ARGS__
#define TWOUT(i, v)

struct TrueT { static constexpr bool value = true; };
struct FalseT { static constexpr bool value = false; };
__device__ __forceinline__ float bf16r(float x) { return __bfloat162float(__float2bfloat16_rn(x)); }
__device__ __forceinline__ float bf_lo(uint32_t u) { return __uint_as_float(u << 16); }
__device__ __forceinline__ float bf_hi(uint32_t u) { return __uint_as_float(u & 0xffff0000u); }
__device__ __forceinline__ uint32_t pack_bf(float lo, float hi) {
    uint32_t r;
    asm("cvt.rn.bf16x2.f32 %0, %1, %2;" : "=r"(r) : "f"(hi), "f"(lo));
    return r;
}
__device__ __forceinline__ uint32_t hmul2_bf(uint32_t a, uint32_t b) {
    uint32_t r;
    asm("mul.rn.bf16x2 %0, %1, %2;" : "=r"(r) : "r"(a), "r"(b));
    return r;
}
__device__ __forceinline__ uint32_t hsub2_bf(uint32_t a, uint32_t b) {
    uint32_t r;
    asm("sub.rn.bf16x2 %0, %1, %2;" : "=r"(r) : "r"(a), "r"(b));
    return r;
}
__device__ __forceinline__ uint32_t smem_u32(const void* p) { return (uint32_t)__cvta_generic_to_shared(p); }
__device__ __forceinline__ uint32_t opaque(uint32_t x) {
    asm volatile("" : "+r"(x));
    return x;
}
__device__ __forceinline__ void trap_if(bool c) {
    asm volatile("{.reg .pred p; setp.ne.u32 p, %0, 0; @p trap;}" ::"r"((uint32_t)c));
}
__device__ __forceinline__ void mbar_init(uint32_t bar, int cnt) {
    asm volatile("mbarrier.init.shared.b64 [%0], %1;" ::"r"(bar), "r"(cnt) : "memory");
}
__device__ __forceinline__ void mbar_arrive(uint32_t bar) {
    asm volatile("mbarrier.arrive.shared.b64 _, [%0];" ::"r"(bar) : "memory");
}
__device__ __forceinline__ void mbar_arrive_if(uint32_t bar, bool pred) {
    asm volatile("{.reg .pred p; setp.ne.u32 p, %1, 0; @p mbarrier.arrive.shared.b64 _, [%0];}" ::"r"(bar), "r"((uint32_t)pred) : "memory");
}
__device__ __forceinline__ void release_if(uint32_t a, uint32_t v, bool pred) {
    asm volatile("{.reg .pred p; setp.ne.u32 p, %2, 0; @p st.relaxed.cta.shared.u8 [%0], %1;}" ::"r"(a), "r"(v), "r"((uint32_t)pred) : "memory");
}
__device__ __forceinline__ uint32_t ld_acq_smem(uint32_t a) {
    uint32_t v;
    asm volatile("ld.relaxed.cta.shared.u32 %0, [%1];" : "=r"(v) : "r"(a) : "memory");
    return v;
}
__device__ __forceinline__ void mbar_expect_tx(uint32_t bar, uint32_t bytes) {
    asm volatile("mbarrier.arrive.expect_tx.shared.b64 _, [%0], %1;" ::"r"(bar), "r"(bytes) : "memory");
}
__device__ __forceinline__ uint32_t mbar_test(uint32_t bar, uint32_t parity) {
    uint32_t ok;
    asm volatile("{.reg .pred p; mbarrier.test_wait.parity.shared.b64 p, [%1], %2; selp.u32 %0, 1, 0, p;}"
                 : "=r"(ok) : "r"(bar), "r"(parity) : "memory");
    return ok;
}
__device__ __forceinline__ void mbar_wait(uint32_t bar, uint32_t parity) {
    asm volatile(
        "{.reg .pred p, q; .reg .u32 c;\n"
        "mbarrier.try_wait.parity.shared.b64 p, [%0], %1;\n"
        "@p bra.uni DONE;\n"
        "mov.u32 c, 0;\n"
        "LOOP:\n"
        "mbarrier.try_wait.parity.shared.b64 p, [%0], %1, 0x4000;\n"
        "@p bra.uni DONE;\n"
        "add.u32 c, c, 1;\n"
        "setp.gt.u32 q, c, 0x100000;\n"
        "@q trap;\n"
        "bra.uni LOOP;\n"
        "DONE:}"
        ::"r"(bar), "r"(parity) : "memory");
}
__device__ __forceinline__ void fence_async_smem() { asm volatile("fence.proxy.async.shared::cta;" ::: "memory"); }
__device__ __forceinline__ void bulk_g2s(uint32_t dst, const void* src, uint32_t bytes, uint32_t bar) {
    asm volatile("cp.async.bulk.shared::cluster.global.mbarrier::complete_tx::bytes [%0], [%1], %2, [%3];"
                 ::"r"(dst), "l"(src), "r"(bytes), "r"(bar) : "memory");
}
__device__ __forceinline__ void bulk_s2g(void* dst, uint32_t src, uint32_t bytes) {
    asm volatile("cp.async.bulk.global.shared::cta.bulk_group [%0], [%1], %2;" ::"l"(dst), "r"(src), "r"(bytes) : "memory");
}
__device__ __forceinline__ void cp16(uint32_t dst, const void* src) {
    asm volatile("cp.async.cg.shared.global [%0], [%1], 16;" ::"r"(dst), "l"(src) : "memory");
}
__device__ __forceinline__ void cp_wait_all() { asm volatile("cp.async.wait_all;" ::: "memory"); }
__device__ __forceinline__ void bar_named(int id, int n) { asm volatile("bar.sync %0, %1;" ::"r"(id), "r"(n) : "memory"); }
__device__ __forceinline__ bool bar_named_or(int id, int n, bool v) {
    uint32_t r;
    asm volatile("{.reg .pred p, q; setp.ne.u32 p, %3, 0; bar.red.or.pred q, %1, %2, p; selp.u32 %0, 1, 0, q;}"
                 : "=r"(r) : "r"(id), "r"(n), "r"((uint32_t)v) : "memory");
    return r;
}
__device__ __forceinline__ uint4 ld_cg_volatile(const uint4* p) {
    uint4 v;
    asm volatile("ld.relaxed.gpu.global.v4.u32 {%0,%1,%2,%3}, [%4];" : "=r"(v.x), "=r"(v.y), "=r"(v.z), "=r"(v.w) : "l"(p) : "memory");
    return v;
}
__device__ __forceinline__ uint32_t ld_acq(const uint32_t* p) {
    uint32_t v;
    asm volatile("ld.acquire.gpu.global.u32 %0, [%1];" : "=r"(v) : "l"(p) : "memory");
    return v;
}
__device__ __forceinline__ uint32_t ld_rlx(const uint32_t* p) {
    uint32_t v;
    asm volatile("ld.relaxed.gpu.global.u32 %0, [%1];" : "=r"(v) : "l"(p) : "memory");
    return v;
}
__device__ __forceinline__ void st_rlx(uint32_t* p, uint32_t v) {
    asm volatile("st.relaxed.gpu.global.u32 [%0], %1;" ::"l"(p), "r"(v) : "memory");
}
__device__ __forceinline__ void fence_acquire() { asm volatile("fence.acquire.gpu;" ::: "memory"); }
__device__ __forceinline__ void fence_release() { asm volatile("fence.release.gpu;" ::: "memory"); }
__device__ __forceinline__ void ldsm_x4(uint32_t* r, uint32_t a) {
    asm volatile("ldmatrix.sync.aligned.m8n8.x4.shared.b16 {%0,%1,%2,%3}, [%4];"
                 : "=r"(r[0]), "=r"(r[1]), "=r"(r[2]), "=r"(r[3]) : "r"(a) : "memory");
}
__device__ __forceinline__ void ldsm_x4_t(uint32_t* r, uint32_t a) {
    asm volatile("ldmatrix.sync.aligned.m8n8.x4.trans.shared.b16 {%0,%1,%2,%3}, [%4];"
                 : "=r"(r[0]), "=r"(r[1]), "=r"(r[2]), "=r"(r[3]) : "r"(a) : "memory");
}
__device__ __forceinline__ void stsm_x4(uint32_t a, const uint32_t* r) {
    asm volatile("stmatrix.sync.aligned.m8n8.x4.shared.b16 [%0], {%1,%2,%3,%4};" ::"r"(a), "r"(r[0]), "r"(r[1]), "r"(r[2]), "r"(r[3]) : "memory");
}
__device__ __forceinline__ void mma16816(float* d, const uint32_t* a, uint32_t b0, uint32_t b1) {
    asm("mma.sync.aligned.m16n8k16.row.col.f32.bf16.bf16.f32 {%0,%1,%2,%3},{%4,%5,%6,%7},{%8,%9},{%0,%1,%2,%3};"
                 : "+f"(d[0]), "+f"(d[1]), "+f"(d[2]), "+f"(d[3])
                 : "r"(a[0]), "r"(a[1]), "r"(a[2]), "r"(a[3]), "r"(b0), "r"(b1));
}
__device__ __forceinline__ void mma1688(float* d, const uint32_t* a, uint32_t b) {
    asm("mma.sync.aligned.m16n8k8.row.col.f32.bf16.bf16.f32 {%0,%1,%2,%3},{%4,%5},{%6},{%0,%1,%2,%3};"
        : "+f"(d[0]), "+f"(d[1]), "+f"(d[2]), "+f"(d[3]) : "r"(a[0]), "r"(a[1]), "r"(b));
}
__device__ __forceinline__ uint32_t hfma2_bf(uint32_t a, uint32_t b, uint32_t c) {
    uint32_t r;
    asm("fma.rn.bf16x2 %0, %1, %2, %3;" : "=r"(r) : "r"(a), "r"(b), "r"(c));
    return r;
}
__device__ __forceinline__ uint4 lds128(uint32_t a) {
    uint4 v;
    asm volatile("ld.shared.v4.u32 {%0,%1,%2,%3}, [%4];" : "=r"(v.x), "=r"(v.y), "=r"(v.z), "=r"(v.w) : "r"(a) : "memory");
    return v;
}
__device__ __forceinline__ uint2 lds64(uint32_t a) {
    uint2 v;
    asm volatile("ld.shared.v2.u32 {%0,%1}, [%2];" : "=r"(v.x), "=r"(v.y) : "r"(a) : "memory");
    return v;
}
__device__ __forceinline__ uint32_t lds32(uint32_t a) {
    uint32_t v;
    asm volatile("ld.shared.u32 %0, [%1];" : "=r"(v) : "r"(a) : "memory");
    return v;
}
__device__ __forceinline__ uint32_t lds16(uint32_t a) {
    uint32_t v;
    asm volatile("{.reg .u16 t; ld.shared.u16 t, [%1]; cvt.u32.u16 %0, t;}" : "=r"(v) : "r"(a) : "memory");
    return v;
}
__device__ __forceinline__ uint32_t lds8(uint32_t a) {
    uint32_t v;
    asm volatile("ld.relaxed.cta.shared.u8 %0, [%1];" : "=r"(v) : "r"(a) : "memory");
    return v;
}
__device__ __forceinline__ void sts16(uint32_t a, uint32_t x) {
    asm volatile("{.reg .u16 t; cvt.u16.u32 t, %1; st.shared.u16 [%0], t;}" ::"r"(a), "r"(x) : "memory");
}
__device__ __forceinline__ void sts32(uint32_t a, uint32_t x) {
    asm volatile("st.shared.u32 [%0], %1;" ::"r"(a), "r"(x) : "memory");
}
__device__ __forceinline__ void sts32f(uint32_t a, float x) {
    asm volatile("st.shared.f32 [%0], %1;" ::"r"(a), "f"(x) : "memory");
}
__device__ __forceinline__ uint32_t atoms_inc(uint32_t a) {
    uint32_t v;
    asm volatile("atom.shared.add.u32 %0, [%1], 1;" : "=r"(v) : "r"(a));
    return v;
}
__device__ __forceinline__ uint32_t atoms_inc_if(uint32_t a, bool pred) {
    uint32_t v = 0xffffffffu;
    asm volatile("{.reg .pred p; setp.ne.u32 p, %2, 0; @p atom.shared.add.u32 %0, [%1], 1;}" : "+r"(v) : "r"(a), "r"((uint32_t)pred));
    return v;
}
__device__ __forceinline__ int warp_scan(int v, int lane) {
#pragma unroll
    for (int o = 1; o < 32; o <<= 1) {
        int t = __shfl_up_sync(~0u, v, o);
        if (lane >= o) v += t;
    }
    return v;
}

constexpr int NCW = 2;
constexpr int NS = 16;
constexpr int CH = 4;
constexpr int CAPK = 384;
constexpr int KB = 160;
constexpr int RPT = 19;
constexpr int SVROW = 528;
constexpr int WROW = 144;
constexpr int TPC = (NTILE + G - 1) / G;

constexpr int SM_RING = 0;
constexpr int SM_RT = SM_RING + NS * 8192;
constexpr int SM_EX = SM_RT + 16384;
constexpr int SM_SORT = SM_EX + NCW * 2 * 4 * 288;
constexpr int SM_PDST = SM_SORT + CAPK * KB;
constexpr int SM_GCNT = SM_PDST + NPG * 128;
constexpr int SM_NCNT = SM_GCNT + 160 * 4;
constexpr int SM_KST = SM_NCNT + 128 * 4;
constexpr int SM_FLAG = SM_KST + 104 * 4;
constexpr int SM_ONES = SM_FLAG + 16;
constexpr int SM_BAR = SM_ONES + CH * KB;
constexpr int SM_REL = SM_BAR + 8;
constexpr int SMEM_BYTES = SM_PDST + 128 * 128;
static_assert(NS + 2 == 18 && SM_BAR % 16 == 0 && SM_BAR + (NS + 2) * 16 <= SMEM_BYTES && CAPK <= 512 && NPG + MAXM + 2 * NCW <= 96 && (SM_BAR - SM_GCNT) / 4 <= 2 * ET, "map");
constexpr int SM_POS = SM_RING;
constexpr int SM_SV = SM_POS + 60160;
constexpr int SM_W = SM_SV + TPC * 16 * SVROW;
constexpr int SM_RAW = SM_W + 2 * 64 * WROW;
constexpr int SM_BINS = SM_SORT;
constexpr int CST_SLOT = 8;
constexpr int SM_CST = SM_RING + CST_SLOT * 8192;
static_assert(SM_CST >= SM_SV && SM_CST + 44 * 512 <= SM_W, "constants");
static_assert(RT_N * 8 <= G * 128 && (SM_ONES - SM_GCNT) / 4 >= ET && SM_RAW + RPT * ET * 4 <= SM_SORT && G * CB * 4 <= CAPK * KB && G == 132 && TPC == 5, "phase 1 map");
static_assert(NPG * 1024 <= NS * 8192, "slow path accumulators live in the ring");
static_assert(NPG <= 96 && SMEM_BYTES <= 232448, "sizes");

#define WG_FENCE() asm volatile("wgmma.fence.sync.aligned;" ::: "memory")
#define WG_COMMIT() asm volatile("wgmma.commit_group.sync.aligned;" ::: "memory")
#define WG_WAIT(n) asm volatile("wgmma.wait_group.sync.aligned %0;" ::"n"(n) : "memory")
#define F8(d, o) "+f"(d[o + 0]), "+f"(d[o + 1]), "+f"(d[o + 2]), "+f"(d[o + 3]), "+f"(d[o + 4]), "+f"(d[o + 5]), "+f"(d[o + 6]), "+f"(d[o + 7])

#define O8(d, o) "=f"(d[o + 0]), "=f"(d[o + 1]), "=f"(d[o + 2]), "=f"(d[o + 3]), "=f"(d[o + 4]), "=f"(d[o + 5]), "=f"(d[o + 6]), "=f"(d[o + 7])
#define KSTEP_ASM(ACC)                                                                                              \
    "{.reg .b64 d, r; .reg .b32 t;\n"                                                                               \
    "or.b32 t, %60, 64; mov.b64 d, {t, 0x40000040};\n"                                                              \
    "wgmma.mma_async.sync.aligned.m64n64k16.f32.bf16.bf16 "                                                         \
    "{%0,%1,%2,%3,%4,%5,%6,%7,%8,%9,%10,%11,%12,%13,%14,%15,%16,%17,%18,%19,%20,%21,%22,%23,%24,%25,%26,%27,%28,"   \
    "%29,%30,%31},{%56,%57,%58,%59},d," ACC ",1,1,1;\n"                                                             \
    "mov.b64 r, {%61, 8}; or.b32 t, %60, 192; mov.b64 d, {t, 0x40000040};\n"                                        \
    "wgmma.mma_async.sync.aligned.m64n16k16.f32.bf16.bf16 {%32,%33,%34,%35,%36,%37,%38,%39},d,r," ACC ",1,1,1,1;\n" \
    "or.b32 t, %60, 320; mov.b64 d, {t, 0x40000040};\n"                                                             \
    "wgmma.mma_async.sync.aligned.m64n16k16.f32.bf16.bf16 {%40,%41,%42,%43,%44,%45,%46,%47},d,r," ACC ",1,1,1,1;\n" \
    "or.b32 t, %60, 448; mov.b64 d, {t, 0x40000040};\n"                                                             \
    "wgmma.mma_async.sync.aligned.m64n16k16.f32.bf16.bf16 {%48,%49,%50,%51,%52,%53,%54,%55},d,r," ACC ",1,1,1,1;}"
template <bool ACC>
__device__ __forceinline__ void kstep_mma(float* T, float* U, const uint32_t* a, uint32_t so) {
    constexpr uint32_t dr0 = ((1024 + SM_RT) >> 4) | (16u << 16);
    if (ACC)
        asm volatile(KSTEP_ASM("1")
                     : F8(T, 0), F8(T, 8), F8(T, 16), F8(T, 24), F8(U, 0), F8(U, 8), F8(U, 16)
                     : "r"(a[0]), "r"(a[1]), "r"(a[2]), "r"(a[3]), "r"(so), "r"(dr0 + (so >> 4)) : "memory");
    else
        asm volatile(KSTEP_ASM("0")
                     : O8(T, 0), O8(T, 8), O8(T, 16), O8(T, 24), O8(U, 0), O8(U, 8), O8(U, 16)
                     : "r"(a[0]), "r"(a[1]), "r"(a[2]), "r"(a[3]), "r"(so), "r"(dr0 + (so >> 4)) : "memory");
}
template <int N> struct IntT { static constexpr int value = N; };

__device__ __forceinline__ void wait_table(uint32_t tag, int lane) {
    for (int it = 0;; it++) {
        bool ok = true;
#pragma unroll
        for (int j = 0; j < 5; j++) {
            const int b = j * 32 + lane;
            if (b < G) ok &= ld_rlx(&g_tflag[b]) == tag;
        }
        if (__all_sync(~0u, ok)) break;
        trap_if(it > (1 << 22));
    }
    fence_acquire();
}

__device__ __forceinline__ void table_tile(unsigned char* sm, int tl, int lane) {
    constexpr uint32_t sb = 1024;
    const int tile = blockIdx.x + tl * G;
    if (tile >= NTILE) return;
    const uint32_t frag = sb + SM_SV + (tl * 16 + (lane & 15)) * SVROW + (lane >> 4) * 16;
    auto put = [&](int x) {
        __syncwarp();
        unsigned char* o = arena_base() + (x >> 1) * WIN + tile * 4096 + (lane >> 3) * 256 + (x & 1) * 128 + (lane & 7) * 16;
        const unsigned char* i = sm + SM_SV + (tl * 16 + (lane >> 3)) * SVROW + x * 128 + (lane & 7) * 16;
#pragma unroll
        for (int r = 0; r < 4; r++) *reinterpret_cast<uint4*>(o + r * 1024) = *reinterpret_cast<const uint4*>(i + r * 4 * SVROW);
    };
    uint32_t a[4][4];
#pragma unroll
    for (int kk = 0; kk < 4; kk++) ldsm_x4(a[kk], frag + kk * 32);
    float acc[8][4];
#pragma unroll
    for (int m = 0; m < 2; m++) {
#pragma unroll
        for (int nt = 0; nt < 8; nt++) acc[nt][0] = acc[nt][1] = acc[nt][2] = acc[nt][3] = 0.f;
        const uint32_t wb = sb + SM_W + m * 64 * WROW + (lane & 15) * WROW + (lane >> 4) * 16;
#pragma unroll
        for (int kk = 0; kk < 4; kk++) {
#pragma unroll
            for (int np = 0; np < 4; np++) {
                uint32_t b[4];
                ldsm_x4_t(b, wb + kk * 16 * WROW + np * 32);
                mma16816(acc[2 * np], a[kk], b[0], b[1]);
                mma16816(acc[2 * np + 1], a[kk], b[2], b[3]);
            }
        }
        if (m == 0) {
#pragma unroll
            for (int nt = 0; nt < 8; nt++) {
                float t[4];
#pragma unroll
                for (int i = 0; i < 4; i++) {
                    const float x = bf16r(acc[nt][i]);
                    t[i] = __fdividef(x, 1.0f + __expf(-x));
                }
                a[nt >> 1][(nt & 1) * 2] = pack_bf(t[0], t[1]);
                a[nt >> 1][(nt & 1) * 2 + 1] = pack_bf(t[2], t[3]);
            }
#pragma unroll
            for (int kk = 0; kk < 4; kk++) stsm_x4(frag + kk * 32, a[kk]);
            put(0);
        }
    }
    uint32_t ph[4][4];
#pragma unroll
    for (int kk = 0; kk < 4; kk++)
#pragma unroll
        for (int i = 0; i < 4; i++) ph[kk][i] = pack_bf(acc[2 * kk + (i >> 1)][2 * (i & 1)], acc[2 * kk + (i >> 1)][2 * (i & 1) + 1]);
#pragma unroll
    for (int x = 1; x < 4; x++) {
        uint32_t v[4][4];
#pragma unroll
        for (int kk = 0; kk < 4; kk++) ldsm_x4(v[kk], frag + x * 128 + kk * 32);
#pragma unroll
        for (int kk = 0; kk < 4; kk++) {
#pragma unroll
            for (int i = 0; i < 4; i++) v[kk][i] = hmul2_bf(v[kk][i], ph[kk][i]);
            stsm_x4(frag + x * 128 + kk * 32, v[kk]);
        }
        put(x);
    }
}

__device__ __forceinline__ bool edge_geom(uint32_t axy, uint32_t az, uint32_t bxy, uint32_t bz, uint32_t& w1, uint32_t& w2) {
    const uint32_t rxy = hsub2_bf(axy, bxy), rz = hsub2_bf(az, bz);
    const uint32_t qxy = hmul2_bf(rxy, rxy), qz = hmul2_bf(rz, rz);
    float q = __uint_as_float(pack_bf(0.f, bf_lo(qxy) + bf_hi(qxy) + bf_lo(qz)));
    q = __uint_as_float(pack_bf(0.f, q + 1e-08f));
    float d, rd;
    asm("sqrt.approx.ftz.f32 %0, %1;" : "=f"(d) : "f"(q));
    const uint32_t du = pack_bf(0.f, d);
    d = __uint_as_float(du);
    asm("rcp.approx.ftz.f32 %0, %1;" : "=f"(rd) : "f"(d));
    w1 = __byte_perm(du, pack_bf(0.f, bf_lo(rxy) * rd), 0x7632);
    w2 = pack_bf(bf_hi(rxy) * rd, bf_lo(rz) * rd);
    return d < D_ACTIVE;
}

__device__ __noinline__ void slow_group(unsigned char* sm, const __nv_bfloat16* sv, const __nv_bfloat16* pos,
                                        const int* src, const int* dst, const __nv_bfloat16* w2,
                                        const __nv_bfloat16* wr, __nv_bfloat16* out, int npg) {
    const int tid = threadIdx.x, lane = tid & 31, grp = blockIdx.x;
    float* acc = reinterpret_cast<float*>(sm);
    for (int i = tid; i < npg * 256; i += CT) acc[i] = 0.f;
    bar_named(1, CT);
    const unsigned short* p16 = reinterpret_cast<const unsigned short*>(pos);
    static_assert(NE % 32 == 0, "");
    for (int e0 = tid - lane; e0 < NE; e0 += CT) {
        const int b = dst[e0 + lane], a = src[e0 + lane];
        uint32_t w1 = 0, w2r = 0;
        bool act = false;
        if (b % G == grp)
            act = edge_geom(p16[3 * a] | (p16[3 * a + 1] << 16), p16[3 * a + 2], p16[3 * b] | (p16[3 * b + 1] << 16),
                            p16[3 * b + 2], w1, w2r);
        for (uint32_t todo = __ballot_sync(~0u, act); todo; todo &= todo - 1) {
            const int l = __ffs(todo) - 1;
            const uint32_t ea = __shfl_sync(~0u, a, l), eb = __shfl_sync(~0u, b, l);
            const uint32_t e1 = __shfl_sync(~0u, w1, l), e2 = __shfl_sync(~0u, w2r, l);
            const unsigned short* row = reinterpret_cast<const unsigned short*>(arena_base()) + (size_t)ea * 128;
            const unsigned short* R = reinterpret_cast<const unsigned short*>(arena_base() + RT_OFF) + ((e1 & 0xffff) - RT_LO + 1) * 16;
            const float rh[3] = {bf_hi(e1), bf_lo(e2), bf_hi(e2)};
            float* o = acc + (eb / G) * 256;
            for (int c = lane; c < 64; c += 32) {
                float ps = 0.f, pr = 0.f, ws = 0.f, wv = 0.f, wvr = 0.f;
                for (int j = 0; j < 64; j++) {
                    const float h = bf_lo(__ldcg(row + j));
                    ps += h * __bfloat162float(w2[j * 192 + c]);
                    pr += h * __bfloat162float(w2[j * 192 + 128 + c]);
                }
                for (int k = 0; k < 16; k++) {
                    const float r = bf_lo(__ldcg(R + k));
                    ws += r * __bfloat162float(wr[k * 192 + c]);
                    wv += r * __bfloat162float(wr[k * 192 + 64 + c]);
                    wvr += r * __bfloat162float(wr[k * 192 + 128 + c]);
                }
                atomicAdd(o + c, ps * ws);
                for (int x = 0; x < 3; x++)
                    atomicAdd(o + 64 + x * 64 + c, bf_lo(__ldcg(row + (x ? WIN / 2 - 64 : 64) + x * 64 + c)) * wv + pr * wvr * rh[x]);
            }
        }
    }
    bar_named(1, CT);
    for (int i = tid; i < npg * 256; i += CT) {
        const size_t o = (size_t)((i >> 8) * G + grp) * 256 + (i & 255);
        out[o] = __float2bfloat16_rn(__bfloat162float(sv[o]) + acc[i]);
    }
}

template <int MODE>
__device__ __forceinline__ void balance(unsigned char* sm, int npg, uint32_t tag, int lane) {
    constexpr uint32_t sb = 1024;
    constexpr int NODE_COST = 2;
    const int blk = blockIdx.x;
    uint32_t* kst = reinterpret_cast<uint32_t*>(sm + SM_KST);
    uint32_t tot = lds32(sb + SM_FLAG), nodes = npg;
    if (MODE == 0) {
        uint32_t key[5];
        for (int it = 0;; it++) {
            bool ok = true;
#pragma unroll
            for (int j = 0; j < 5; j++) {
                key[j] = ~0u;
                if (j * 32 + lane < G) {
                    key[j] = ld_rlx(&g_kcnt[j * 32 + lane]);
                    ok &= (key[j] >> 21) == tag;
                    key[j] = ((key[j] & 511) << 8) | (j * 32 + lane);
                }
            }
            if (__all_sync(~0u, ok)) break;
            __nanosleep(200);
            trap_if(it > (1 << 22));
        }
        auto below = [&](uint32_t x) {
            uint32_t c = 0;
#pragma unroll
            for (int j = 0; j < 5; j++) c += key[j] < x;
            return __reduce_add_sync(~0u, c);
        };
        const uint32_t mine = (tot << 8) | blk, want = G - 1 - below(mine);
        uint32_t other = 0;
#pragma unroll 1
        for (uint32_t bit = 1u << 16; bit; bit >>= 1)
            if (below(other | bit) <= want) other |= bit;
        const uint32_t ok = other >> 8, ob = other & 255;
        if (ok != 0 && mine > other) {
            uint32_t m = 0, t0 = tot;
            while (m < MAXM) {
                const uint32_t s = kst[npg - 1 - m] & 511;
                const uint32_t moved = tot - t0 + m * NODE_COST, c = t0 - s + NODE_COST;
                if (2 * moved + c > tot - ok || tot - s > MAXB || ok + tot - s > CAPK - CH) break;
                t0 = s;
                m++;
            }
#pragma unroll 1
            for (uint32_t i = lane; i < (tot - t0) * 10; i += 32)
                g_mail[ob][2 + i] = reinterpret_cast<const uint4*>(sm + SM_SORT + t0 * KB)[i];
            if (lane < m) reinterpret_cast<uint32_t*>(g_mail[ob])[lane] = kst[npg - m + lane] + (ok - t0) * 513;
            __syncwarp();
            if (lane == 0) {
                fence_release();
                st_rlx(&g_mflag[ob], m | ((tot - t0) << 8) | (tag << 21));
            }
            tot = t0;
            nodes -= m;
        } else if (ok != 0) {
            uint32_t v;
            for (int it = 0; ((v = ld_rlx(&g_mflag[blk])) >> 21) != tag; it++) {
                __nanosleep(100);
                trap_if(it > (1 << 22));
            }
            fence_acquire();
            __syncwarp();
            if (lane == 0) g_mflag[blk] = 0;
            const uint32_t m = v & 255, nb = (v >> 8) & 255;
#pragma unroll 1
            for (uint32_t i = lane; i < nb * 10; i += 32)
                reinterpret_cast<uint4*>(sm + SM_SORT + tot * KB)[i] = __ldcg(&g_mail[blk][2 + i]);
            if (lane < m) kst[npg + lane] = __ldcg(reinterpret_cast<const uint32_t*>(g_mail[blk]) + lane);
            tot += nb;
            nodes += m;
        }
    }
    if (lane == 0) {
        sts32(sb + SM_FLAG + 4, tot);
        sts32(sb + SM_FLAG + 8, nodes);
    }
    mbar_arrive(sb + SM_BAR + (NS + 1) * 16);
}

template <int MODE>
__global__ void __launch_bounds__(THREADS, 1)
painn_kernel(const __nv_bfloat16* __restrict__ sv, const __nv_bfloat16* __restrict__ pos,
             const int* __restrict__ src, const int* __restrict__ dst,
             const __nv_bfloat16* __restrict__ freqs, const __nv_bfloat16* __restrict__ w1,
             const __nv_bfloat16* __restrict__ w2, const __nv_bfloat16* __restrict__ wr,
             __nv_bfloat16* __restrict__ out) {
    extern __shared__ __align__(1024) unsigned char sm[];
    const int tid = threadIdx.x, lane = tid & 31;
    const int warp = __shfl_sync(~0u, tid >> 5, 0), wg = warp >> 2;
    const int blk = blockIdx.x;
    constexpr uint32_t sb = 1024;
    constexpr uint32_t bar_cst = sb + SM_BAR + NS * 16, bar_pos = bar_cst + 8, bar_fin = bar_cst + 16;
    STAMP(0);

    const int npg = (NN - blk + G - 1) / G;
    uint32_t tag;
    bool slow = false;
    if (warp >= 11) {
        const int tw = warp - 11, tt = tid - ET;
        trap_if(smem_u32(sm) != sb);
        if (MODE != 1 && warp == 15) {
            if (lane == 0) {
                mbar_init(bar_pos, 1);
                fence_async_smem();
                mbar_expect_tx(bar_pos, NN * 6);
                bulk_g2s(sb + SM_POS, pos, NN * 6, bar_pos);
            }
            asm volatile("bar.arrive 6, %0;" ::"n"(ET + 32) : "memory");
        }
        tag = ld_rlx(&g_epoch) + 1u;
        if (MODE != 2) {
            const uint32_t f2 = __ldg(reinterpret_cast<const uint32_t*>(freqs) + (tt & 7));
            for (int i = tt; i < 1024; i += 160) {
                const int m = i >> 9, r = (i >> 3) & 63, c = i & 7;
                cp16(sb + SM_W + (m * 64 + r) * WROW + c * 16, m == 0 ? w1 + r * 64 + c * 8 : w2 + r * 192 + 64 + c * 8);
            }
            asm volatile("cp.async.commit_group;" ::: "memory");
            const int tile = blk + tw * G;
            if (tile < NTILE) {
#pragma unroll
                for (int i = 0; i < 16; i++)
                    cp16(sb + SM_SV + (tw * 16 + i) * SVROW + lane * 16, sv + (size_t)(tile * 16 + i) * 256 + lane * 8);
            }
            asm volatile("cp.async.commit_group;" ::: "memory");
            if (blk == G - 1 && tt < 8) reinterpret_cast<uint32_t*>(arena_base() + RT_OFF)[tt] = 0u;
            if (const int i = blk * 128 + tt; tt < 128 && i < RT_N * 8) {
                const float d = __uint_as_float((uint32_t)(RT_LO + (i >> 3)) << 16);
                const float arg = bf16r(__fdividef(bf16r(3.14159265358979f * d), 5.0f));
                const float fc = bf16r(0.5f * bf16r(bf16r(cosf(arg)) + 1.0f));
                float sn[2] = {bf16r(d * bf_lo(f2)), bf16r(d * bf_hi(f2))};
#pragma unroll 1
                for (int k = 0; k < 2; k++) {
                    const float x = sinf(sn[0]);
                    sn[0] = sn[1];
                    sn[1] = x;
                }
                const float r0 = bf16r(__fdividef(bf16r(sn[0]), d)) * fc;
                const float r1 = bf16r(__fdividef(bf16r(sn[1]), d)) * fc;
                reinterpret_cast<uint32_t*>(arena_base() + RT_OFF)[i + 8] = pack_bf(r0, r1);
            }
            STAMP(10);
            asm volatile("cp.async.wait_group 1;" ::: "memory");
            bar_named(2, 160);
            cp_wait_all();
            __syncwarp();
            STAMP(1);
            table_tile(sm, tw, lane);
            STAMP(2);
            bar_named(2, 160);
            if (tid == THREADS - 32) {
                fence_release();
                st_rlx(&g_tflag[blk], tag);
            }
            __syncwarp();
            STAMP(3);
        }
        if (MODE != 1 && warp == 15) wait_table(tag, lane);
        if (MODE != 1 && warp < 15) {
            const int w = tw, g = lane >> 2, q = lane & 3;
            uint4* cst = reinterpret_cast<uint4*>(sm + SM_CST) + lane;
            auto quad = [&](const uint32_t* x, int koff) {
                const uint32_t a0 = __ldg(x + koff * 96), a1 = __ldg(x + (koff + 1) * 96);
                const uint32_t b0 = __ldg(x + (koff + 8) * 96), b1 = __ldg(x + (koff + 9) * 96);
                return make_uint4(__byte_perm(a0, a1, 0x5410), __byte_perm(a0, a1, 0x7632),
                                  __byte_perm(b0, b1, 0x5410), __byte_perm(b0, b1, 0x7632));
            };
#pragma unroll
            for (int v = 0; v < 2; v++) {
#pragma unroll
                for (int kk = 0; kk < 4; kk++)
                    cst[(v * 20 + w * 4 + kk) * 32] = quad(reinterpret_cast<const uint32_t*>(w2 + v * 128) + w * 8 + g, 16 * kk + 2 * q);
                cst[(v * 20 + 16 + w) * 32] = quad(reinterpret_cast<const uint32_t*>(wr + v * 128) + w * 8 + g, 2 * q);
            }
            const unsigned short* wrp = reinterpret_cast<const unsigned short*>(wr) + 64 + 16 * w + g + 2 * q * 192;
            uint32_t x[4];
#pragma unroll
            for (int i = 0; i < 4; i++) {
                const unsigned short* y = wrp + (i >> 1) * 8 * 192 + (i & 1) * 8;
                x[i] = (uint32_t)__ldg(y) | ((uint32_t)__ldg(y + 192) << 16);
            }
            cst[(40 + w) * 32] = make_uint4(x[0], x[1], x[2], x[3]);
            if (const int i = (warp - 12) * 6 + lane; warp >= 12 && lane < 6) {
                mbar_init(sb + SM_BAR + i * 16, i == NS ? NCW * 128 : 32);
                if (i < NS) sts32(sb + SM_REL + i * 16, 0);
            }
        }
    } else {
    uint32_t es[EPT], ed[EPT];
    bool tail = false;
    if (MODE != 2) {
#pragma unroll
        for (int r = 0; r < EV; r++) {
            const int gi = (blk * EV + r) * ET + tid;
            const int4 d4 = __ldcs(reinterpret_cast<const int4*>(dst) + gi);
            const int4 s4 = __ldcs(reinterpret_cast<const int4*>(src) + gi);
            es[4 * r] = s4.x; es[4 * r + 1] = s4.y; es[4 * r + 2] = s4.z; es[4 * r + 3] = s4.w;
            ed[4 * r] = d4.x; ed[4 * r + 1] = d4.y; ed[4 * r + 2] = d4.z; ed[4 * r + 3] = d4.w;
        }
        const int te = E_VEC / 2 + blk * E_TAIL + tid;
        tail = tid < E_TAIL && te < NE / 2;
        int2 s2 = make_int2(0, 0), d2 = make_int2(0, 0);
        if (tail) {
            d2 = __ldcs(reinterpret_cast<const int2*>(dst) + te);
            s2 = __ldcs(reinterpret_cast<const int2*>(src) + te);
        }
        es[EPT - 2] = s2.x; es[EPT - 1] = s2.y;
        ed[EPT - 2] = d2.x; ed[EPT - 1] = d2.y;
    }
    tag = ld_rlx(&g_epoch) + 1u;
    if (MODE != 2 && tid < 136) st_rlx(&g_xcnt[blk * 160 + tid], 0u);
    if (MODE != 1) {
        if (tid >= 160 && tid < 160 + 48) asm volatile("prefetch.global.L2 [%0];" ::"l"(wr + (tid - 160) * 64));
        if (tid >= 224) asm volatile("prefetch.global.L2 [%0];" ::"l"(w2 + ((tid - 224) >> 1) * 192 + (tid & 1) * 128));
    }
    sts32(sb + SM_GCNT + tid * 4, 0u);
    if (const int i = tid + ET; i < (SM_BAR - SM_GCNT) / 4)
        sts32(sb + SM_GCNT + i * 4, i >= (SM_ONES - SM_GCNT) / 4 ? 0x3f803f80u : 0u);
    bar_named(1, ET);
    if (MODE != 2) {
        uint32_t rk[EPT];
#pragma unroll
        for (int i = 0; i < EPT; i++) {
            const uint32_t dl = ed[i] / G;
            ed[i] -= dl * G;
            es[i] |= (dl << 14) | (tag << 21);
            rk[i] = atoms_inc_if(sb + SM_GCNT + ed[i] * 4, i < EPT - 2 || tail);
        }
#pragma unroll
        for (int i = 0; i < EPT; i++)
            if (rk[i] < CB) reinterpret_cast<uint32_t*>(sm + SM_BINS)[ed[i] * CB + rk[i]] = es[i];
        STAMP(2);
        bar_named(1, ET);
        {
            const uint32_t c = lane & 15;
            uint32_t cnt[6];
            uint4 v[6];
#pragma unroll
            for (int j = 0; j < 6; j++) {
                const uint32_t g = (j * 11 + warp) * 2 + (lane >> 4);
                cnt[j] = reinterpret_cast<const uint32_t*>(sm + SM_GCNT)[g];
                v[j] = reinterpret_cast<const uint4*>(sm + SM_BINS)[g * (CB / 4) + c];
            }
            auto put = [&](uint4 x, uint32_t g, uint32_t k, uint32_t n) {
                const uint32_t pad = (tag << 21) | 0x1fffff;
                if (k * 4 >= n) x.x = pad;
                if (k * 4 + 1 >= n) x.y = pad;
                if (k * 4 + 2 >= n) x.z = pad;
                if (k * 4 + 3 >= n) x.w = pad;
                __stcg(&g_xrec[(g * G + blk) * (CB / 4) + k], x);
            };
            bool big = false;
#pragma unroll
            for (int j = 0; j < 6; j++) {
                if ((c & 14) * 4 < cnt[j]) put(v[j], (j * 11 + warp) * 2 + (lane >> 4), c, cnt[j]);
                big |= cnt[j] > 64;
            }
            if (big) {
#pragma unroll 1
                for (int j = 0; j < 6; j++) {
                    const uint32_t g = (j * 11 + warp) * 2 + (lane >> 4);
                    const uint32_t n = reinterpret_cast<const uint32_t*>(sm + SM_GCNT)[g];
                    if (n > 64 && c < CB / 4 - 16) put(reinterpret_cast<const uint4*>(sm + SM_BINS)[g * (CB / 4) + 16 + c], g, 16 + c, n);
                }
            }
            if (tid < 136) st_rlx(&g_xcnt[blk * 160 + tid], reinterpret_cast<const uint32_t*>(sm + SM_GCNT)[tid] | (tag << 21));
        }
        STAMP(3);
    }
    if (MODE != 1) bar_named(6, ET + 32);

    if (MODE != 1) {
        for (int i = tid; i < CAPK * KB / 16; i += ET) reinterpret_cast<uint4*>(sm + SM_SORT)[i] = make_uint4(0, 0, 0, 0);
        mbar_wait(bar_pos, 0);
        for (int i = tid; i < npg * 16; i += ET) {
            const unsigned short* pn = reinterpret_cast<const unsigned short*>(sm + SM_POS) + ((i >> 4) * G + blk) * 3;
            reinterpret_cast<uint2*>(sm + SM_PDST)[i] = make_uint2(pn[0] | (pn[1] << 16), pn[2]);
        }
        bar_named(1, ET);
    }
    if (MODE != 1) {
    STAMP(4);
    uint32_t r0[RPT], w1e[RPT], w2e[RPT], rk[RPT];
    int tot_k = 0;
    uint32_t nrec = 0;
    {
        uint32_t mine = tag << 21;
        for (int it = 0;; it++) {
            if (lane < 12) mine = ld_rlx(&g_xcnt[(warp * 12 + lane) * 160 + blk]);
            if (__all_sync(~0u, (mine >> 21) == tag)) break;
            trap_if(it > (1 << 22));
        }
        STAMP(5);
        mine &= 0x1fffff;
        const uint32_t h = lane >> 4, c = lane & 15;
        const uint4* xr = g_xrec + (blk * G + warp * 12 + h) * (CB / 4) + c;
        uint4 v[6];
        uint32_t cnt[6];
#pragma unroll
        for (int j = 0; j < 6; j++) {
            cnt[j] = __shfl_sync(~0u, mine, 2 * j + h);
            v[j].x = v[j].y = v[j].z = v[j].w = tag << 21;
            if (c * 4 < cnt[j]) v[j] = ld_cg_volatile(xr + j * 2 * (CB / 4));
        }
        const uint32_t nch = (mine + 3) >> 2, incl = warp_scan(nch, lane);
        const uint32_t total = __shfl_sync(~0u, incl, 31) * 4, base = incl - nch;
        slow = total > RPT * 32 || __any_sync(~0u, mine > CB);
        uint4* raw = reinterpret_cast<uint4*>(sm + SM_RAW) + warp * (RPT * 8);
        auto stale = [&](const uint4& x) {
            const uint32_t tg = tag << 21;
            return ((x.x ^ tg) | (x.y ^ tg) | (x.z ^ tg) | (x.w ^ tg)) >> 21;
        };
        for (int it = 0;; it++) {
            uint32_t bad = 0;
#pragma unroll
            for (int j = 0; j < 6; j++) bad |= stale(v[j]);
            if (!__any_sync(~0u, bad)) break;
#pragma unroll
            for (int j = 0; j < 6; j++)
                if (c * 4 < cnt[j]) v[j] = ld_cg_volatile(xr + j * 2 * (CB / 4));
            trap_if(it > (1 << 22));
        }
        STAMP(1);
        if (!slow) {
#pragma unroll
            for (int j = 0; j < 6; j++) {
                const uint32_t o = __shfl_sync(~0u, base, 2 * j + h);
                if (c * 4 < cnt[j]) raw[o + c] = v[j];
            }
            if (__any_sync(~0u, mine > 64)) {
#pragma unroll 1
                for (int j = 0; j < 6; j++) {
                    const uint32_t o = __shfl_sync(~0u, base, 2 * j + h), n = __shfl_sync(~0u, mine, 2 * j + h);
                    if ((16 + c) * 4 < n) {
                        uint4 x;
                        for (int it = 0;; it++) {
                            x = ld_cg_volatile(xr + j * 2 * (CB / 4) + 16);
                            if (!stale(x)) break;
                            trap_if(it > (1 << 22));
                        }
                        raw[o + 16 + c] = x;
                    }
                }
            }
            __syncwarp();
            auto geom = [&](int i) {
                const uint32_t r = reinterpret_cast<const uint32_t*>(raw)[i * 32 + lane];
                const uint32_t a = min(r & 0x3fff, NN - 1u);
                const uint32_t* pa = reinterpret_cast<const uint32_t*>(sm + SM_POS + ((a * 6) & ~3u));
                const uint32_t a0 = pa[0], a1 = pa[1];
                const uint2 pb = *reinterpret_cast<const uint2*>(sm + SM_PDST + ((r >> 7) & (127 << 7)) + (lane & 15) * 8);
                const bool act = edge_geom(__funnelshift_r(a0, a1, a << 4), __funnelshift_r(a1, 0u, a << 4), pb.x, pb.y, w1e[i], w2e[i]);
                r0[i] = act && (r & 0x3fff) != 0x3fff && i * 32 + lane < total ? r & 0x1fffff : 0xffffffffu;
            };
#pragma unroll
            for (int i = 0; i < 14; i++) geom(i);
#pragma unroll
            for (int i = 14; i < RPT; i++) r0[i] = 0xffffffffu;
            if (total > 14 * 32) {
                geom(14);
                geom(15);
                if (total > 16 * 32) {
#pragma unroll
                    for (int i = 16; i < RPT; i++) geom(i);
                }
            }
            nrec = total;
#pragma unroll
            for (int i = 0; i < RPT; i++)
                if (i < 14 || i * 32 < total) rk[i] = atoms_inc(sb + SM_NCNT + min(r0[i] >> 14, 96u + lane) * 4);
        }
    }
    STAMP(6);
    slow = bar_named_or(1, ET, slow);
    if (tag == TAGMAX && !slow)
        for (int i = tid; i < G * CB / 4; i += ET) g_xrec[blk * G * (CB / 4) + i] = make_uint4(0, 0, 0, 0);
    if (!slow) {
        STAMP(10);
        {
            int k[4], s = 0;
#pragma unroll
            for (int j = 0; j < 3; j++) {
                k[j] = s;
                s += max((reinterpret_cast<const uint32_t*>(sm + SM_NCNT)[lane * 3 + j] + 15) >> 4, lane * 3 + j < npg ? 1u : 0u);
            }
            k[3] = s;
            const int incl = warp_scan(s, lane);
            tot_k = __shfl_sync(~0u, incl, 31);
#pragma unroll
            for (int j = 0; j < 3; j++)
                reinterpret_cast<uint32_t*>(sm + SM_KST)[lane * 3 + j] =
                    ((incl - s + k[j]) & 511) | (((incl - s + k[j + 1]) & 511) << 9) | (((lane * 3 + j) * G + blk) << 18);
            __syncwarp();
        }
        slow = tot_k > CAPK - CH;
        if (!slow) {
#pragma unroll
            for (int i = 0; i < RPT; i++) {
                if (i < 14 || i * 32 < nrec) {
                    const uint32_t ks = reinterpret_cast<const uint32_t*>(sm + SM_KST)[min(r0[i] >> 14, 96u)] & 511;
                    const uint32_t e = rk[i] & 15, kb = sb + SM_SORT + (ks + (rk[i] >> 4)) * KB;
                    rk[i] = kb + 8 * ((e & 7) >> 1) + 2 * (e & 1) + 4 * (e >> 3);
                    asm volatile("{.reg .pred p; .reg .u16 a; setp.ne.u32 p, %1, 0xffffffff;\n"
                                 "cvt.u16.u32 a, %2; @p st.shared.u16 [%0], a;\n"
                                 "cvt.u16.u32 a, %3; @p st.shared.u16 [%0 + 32], a;}"
                                 ::"r"(kb + e * 2), "r"(r0[i]), "r"((r0[i] & 0x3fff) + 1), "r"(w1e[i] - (RT_LO - 1)));
                }
            }
        }
    }
    if (tid == 0) {
        sts32(sb + SM_FLAG, slow ? 0 : tot_k);
        if (MODE == 0) st_rlx(&g_kcnt[blk], (slow ? 0 : tot_k) | (tag << 21));
    }
    asm volatile("bar.arrive 5, %0;" ::"n"(ET + 128) : "memory");
    if (!slow) {
#pragma unroll
        for (int i = 0; i < RPT; i++) {
            if (i < 14 || i * 32 < nrec)
                asm volatile("{.reg .pred p; .reg .u16 a, b; setp.ne.u32 p, %1, 0xffffffff;\n"
                             "mov.b32 {a, b}, %2; @p st.shared.u16 [%0 + 64], b;\n"
                             "mov.b32 {a, b}, %3; @p st.shared.u16 [%0 + 96], a; @p st.shared.u16 [%0 + 128], b;}"
                             ::"r"(rk[i]), "r"(r0[i]), "r"(w1e[i]), "r"(w2e[i]));
        }
    }
    STAMP(7);
    }
    }
    if (MODE == 1) return;

    if (wg == 3) {
        asm volatile("setmaxnreg.dec.sync.aligned.u32 56;");
        STAMP(4);
        asm volatile("bar.arrive 7, %0;" ::"n"(THREADS) : "memory");
        bar_named(5, ET + 128);
        if (MODE == 0 && blk == 0 && tid == CT) g_epoch = tag % TAGMAX;
        {
            uint32_t tot = lds32(sb + SM_FLAG) ? lds32(sb + SM_KST + (npg - MAXM) * 4) & 511 : 0;
            const uint64_t ab = reinterpret_cast<uint64_t>(arena_base());
            const uint32_t ahi = (uint32_t)((ab + (lane >> 4) * WIN) >> 32);
            const uint32_t acst = (uint32_t)(ab + (lane >> 4) * WIN) | ((lane & 15) * 16);
            const uint32_t rlo = (uint32_t)(ab + RT_OFF) + (lane & 1) * 16, rhi = (uint32_t)(ab >> 32);
            const uint32_t dlane = __shfl_sync(~0u, sb + SM_RING + (lane >> 3) * 2048 + (lane & 7) * 16, lane);
            const uint32_t rlane = __shfl_sync(~0u, sb + SM_RT + (lane & 1) * 128 + (lane >> 4) * 256 + ((lane >> 1) & 7) * 16, lane);
            const uint32_t zl = __shfl_sync(~0u, tid >> 9, lane);
            const unsigned char* slds = sm + SM_SORT + zl;
            const unsigned char* dlds = sm + SM_SORT + 32 + (lane >> 1) * 2;
            auto gather = [&](uint32_t dst, uint32_t sw, int hi) {
                asm volatile("{.reg .b64 a; mov.b64 a, {%1, %2}; cp.async.cg.shared.global [%0], [a + -256], 16;}"
                             ::"r"(dst), "r"(__byte_perm(sw, acst, hi ? 0x7324 : 0x7104)), "r"(ahi));
            };
            auto gather_if = [&](uint32_t dst, uint32_t sw, int hi) {
                asm volatile("{.reg .b64 a; .reg .pred p; setp.gt.u32 p, %3, %4; mov.b64 a, {%1, %2};\n"
                             "@p cp.async.cg.shared.global [%0], [a + -256], 16;}"
                             ::"r"(dst), "r"(__byte_perm(sw, acst, hi ? 0x7324 : 0x7104)), "r"(ahi), "r"(sw), "r"(hi ? 0xffffu : 0u));
            };
            STAMP(8);
            uint32_t tw0 = 0, tw1 = 0, tw2 = 0;
            struct Step { uint4 sa, sc; uint32_t di, rel; };
            auto fetch = [&](Step& x, uint32_t t) {
                x.sa = *reinterpret_cast<const uint4*>(slds + t * KB);
                x.sc = *reinterpret_cast<const uint4*>(slds + t * KB + 16);
                x.di = *reinterpret_cast<const unsigned short*>(dlds + t * KB);
                x.rel = ld_acq_smem(sb + SM_REL + (t & (NS - 1)) * 16 + zl);
            };
            auto run = [&](const Step& x, uint32_t t, auto first, auto&& prefetch) {
                const uint32_t slot = t & (NS - 1), need = (t / NS) * 0x01010101u;
                const uint32_t d0 = dlane + slot * 8192;
                const uint32_t s8[8] = {x.sa.x, x.sa.y, x.sa.z, x.sa.w, x.sc.x, x.sc.y, x.sc.z, x.sc.w};
                if (decltype(first)::value) {
                    if (t >= CST_SLOT) mbar_wait(bar_cst, 0);
#pragma unroll
                    for (int e = 0; e < 16; e++)
                        if (!(s8[e >> 1] >> (16 * (e & 1))))
                            asm volatile("cp.async.cg.shared.global [%0], [%1], 16, 0;" ::"r"(d0 + e * 128), "l"(ab));
                } else if (__any_sync(~0u, x.rel != need)) {
                    TW(tw0, for (int it = 0; ld_acq_smem(sb + SM_REL + slot * 16) != need; it++) {
                        __nanosleep(32);
                        trap_if(it > (1 << 24));
                    });
                }
                prefetch();
                asm volatile("{.reg .b64 a; mov.b64 a, {%1, %2}; cp.async.ca.shared.global [%0], [a], 16;}"
                             ::"r"(rlane + slot * 512), "r"(rlo + x.di * 32), "r"(rhi));
                if (!decltype(first)::value && __any_sync(~0u, x.sc.w >> 16)) {
#pragma unroll
                    for (int e = 0; e < 16; e++) gather((d0 ^ ((e & 7) << 4)) + e * 128, s8[e >> 1], e & 1);
                } else {
#pragma unroll
                    for (int e = 0; e < 16; e++) gather_if((d0 ^ ((e & 7) << 4)) + e * 128, s8[e >> 1], e & 1);
                }
                asm volatile("cp.async.mbarrier.arrive.noinc.shared.b64 [%0];" ::"r"(sb + SM_BAR + slot * 16) : "memory");
            };
            uint32_t t = warp & 3;
            Step x, y;
#pragma unroll 1
            for (; t < min(tot, (uint32_t)NS); t += 4) {
                fetch(x, t);
                run(x, t, TrueT(), [] {});
            }
#pragma unroll 1
            for (int part = 0; part < 2 && tot; part++) {
                fetch(x, t);
#pragma unroll 1
                while (t < tot) {
                    run(x, t, FalseT(), [&] { fetch(y, t + 4); });
                    t += 4;
                    if (t >= tot) break;
                    run(y, t, FalseT(), [&] { fetch(x, t + 4); });
                    t += 4;
                }
                mbar_wait(bar_fin, 0);
                tot = lds32(sb + SM_FLAG + 4);
            }
            cp_wait_all();
            STAMP(9);
            TWOUT(0, tw0); TWOUT(1, tw1); TWOUT(2, tw2);
        }
        return;
    }

    bar_named(7, THREADS);
    if (lds32(sb + SM_FLAG) == 0) {
        slow_group(sm, sv, pos, src, dst, w2, wr, out, npg);
        if (tag == TAGMAX)
            for (int i = tid; i < G * CB / 4; i += CT) g_xrec[blk * G * (CB / 4) + i] = make_uint4(0, 0, 0, 0);
        return;
    }

    if (wg == 2) {
        asm volatile("setmaxnreg.dec.sync.aligned.u32 24;");
        if (warp == 8) balance<MODE>(sm, npg, tag, lane);
        return;
    }
    asm volatile("setmaxnreg.inc.sync.aligned.u32 216;");
    {
        const int w = warp & 3, g = lane >> 2, q = lane & 3;
        uint32_t wa[4][4][4];
        uint32_t cy[4][4], cu[4];
#pragma unroll
        for (int i = 0; i < 21; i++) {
            const uint4 x = lds128(sb + SM_CST + ((i == 20 ? 40 + w : (w ? 20 : 0) + i) * 32 + lane) * 16);
            uint32_t* y = i < 16 ? wa[i >> 2][i & 3] : i < 20 ? cy[i - 16] : cu;
            y[0] = x.x; y[1] = x.y; y[2] = x.z; y[3] = x.w;
        }
        mbar_arrive(bar_cst);
        static_assert(sb + SM_RING == 1024, "descriptor constants");
        const uint32_t l3 = __shfl_sync(~0u, lane & 3, lane);
        const uint32_t rt_lane = __shfl_sync(~0u, sb + SM_RT + lane * 16, lane);
        const uint32_t rh_lane = __shfl_sync(~0u, w ? sb + SM_SORT + 32 + w * 32 + q * 8 : sb + SM_ONES, lane);
        const uint32_t rh_step = w ? KB : 0;
        const uint32_t ex_w = __shfl_sync(~0u, sb + SM_EX + wg * 2304 + q * 288 + (16 * w + g) * 4, lane);
        const uint32_t ex_r = __shfl_sync(~0u, sb + SM_EX + wg * 2304 + w * 288 + (16 * q + 2 * g) * 4, lane);
        uint32_t one[4];
#pragma unroll
        for (int i = 0; i < 4; i++) one[i] = __shfl_sync(~0u, g == 2 * i ? 0x3f803f80u : 0u, lane);
        int id0 = wg * G + blk, d1 = 0, d2 = 0;
        const uint32_t* svp = reinterpret_cast<const uint32_t*>(sv) + id0 * 128 + w * 32 + q * 8 + g;
        uint32_t* outp = reinterpret_cast<uint32_t*>(out) + id0 * 128 + w * 32 + q * 8 + g;
        uint32_t t = 0, tend = 0, exo = 0, res = 0, tw0 = 0;
        int n = wg;
        uint32_t A[CH][4], aY[4][2], so[CH];
        uint2 rh[CH] = {};
        float T[32], U[24], Y[4][8], o[4] = {0.f, 0.f, 0.f, 0.f};
        auto weigh = [&](const float* y, const uint32_t* c, uint32_t* a) {
#pragma unroll
            for (int r = 0; r < 2; r++)
                a[r] = hfma2_bf(pack_bf(y[4 + 2 * r], y[5 + 2 * r]), c[2 + r], hmul2_bf(pack_bf(y[2 * r], y[2 * r + 1]), c[r]));
        };
        auto prep_load = [&]() {
            const uint32_t ha = rh_lane + t * rh_step;
#pragma unroll
            for (int i = 0; i < CH; i++) so[i] = ((t + i) & (NS - 1)) * 512;
#pragma unroll
            for (int i = 0; i < CH - 1; i++)
                asm volatile("{.reg .pred p; setp.gt.u32 p, %8, 2;\n"
                             "@p ldmatrix.sync.aligned.m8n8.x4.trans.shared.b16 {%0,%1,%2,%3}, [%6];\n"
                             "ld.shared.v2.u32 {%4,%5}, [%7];}"
                             : "+r"(A[i][0]), "+r"(A[i][1]), "+r"(A[i][2]), "+r"(A[i][3]), "=r"(rh[i].x), "=r"(rh[i].y)
                             : "r"(rt_lane + so[i]), "r"(ha + i * KB), "r"(i < 2 ? tend - t + 2 : tend - t) : "memory");
            asm volatile("{.reg .pred p; setp.gt.u32 p, %8, 3;\n"
                         "@p ldmatrix.sync.aligned.m8n8.x4.trans.shared.b16 {%0,%1,%2,%3}, [%6];\n"
                         "@p ld.shared.v2.u32 {%4,%5}, [%7];}"
                         : "+r"(A[3][0]), "+r"(A[3][1]), "+r"(A[3][2]), "+r"(A[3][3]), "+r"(rh[3].x), "+r"(rh[3].y)
                         : "r"(rt_lane + so[3]), "r"(ha + 3 * KB), "r"(tend - t) : "memory");
        };
        auto prep_mul = [&]() {
#pragma unroll
            for (int i = 0; i < CH; i++)
                asm volatile("mul.rn.bf16x2 %0, %0, %4; mul.rn.bf16x2 %1, %1, %4; mul.rn.bf16x2 %2, %2, %5; mul.rn.bf16x2 %3, %3, %5;"
                             : "+r"(A[i][0]), "+r"(A[i][1]), "+r"(A[i][2]), "+r"(A[i][3]) : "r"(rh[i].x), "r"(rh[i].y));
        };
        uint32_t slot_addr, slot_lap;
        auto locate = [&]() {
            const uint32_t tl = min(t + l3, tend - 1);
            slot_addr = sb + SM_BAR + (tl & (NS - 1)) * 16;
            slot_lap = tl / NS;
        };
        auto lane_ready = [&]() {
            const uint32_t rel = lds8(slot_addr + 8 + w);
            const uint32_t full = mbar_test(slot_addr, slot_lap & 1);
            return rel == slot_lap && full;
        };
        auto wait_chunk = [&]() {
            TW(tw0, asm volatile(
                "{.reg .pred p, q; .reg .u32 c, r;\n"
                "mov.u32 c, 0;\n"
                "LOOP:\n"
                "ld.relaxed.cta.shared.u8 r, [%0];\n"
                "mbarrier.try_wait.parity.shared.b64 p, [%1], %3;\n"
                "setp.eq.and.u32 p, r, %2, p;\n"
                "vote.sync.all.pred p, p, 0xffffffff;\n"
                "@p bra.uni DONE;\n"
                "add.u32 c, c, 1;\n"
                "setp.gt.u32 q, c, 0x400000;\n"
                "@q trap;\n"
                "bra.uni LOOP;\n"
                "DONE:}"
                ::"r"(slot_addr + 8 + w), "r"(slot_addr), "r"(slot_lap), "r"(slot_lap & 1) : "memory"));
            prep_load();
            prep_mul();
        };
        auto issue = [&](auto first) {
            const uint32_t rem = tend - t;
            asm volatile("fence.proxy.async::generic.acquire.sync_restrict::shared::cluster.cluster;" ::: "memory");
            WG_FENCE();
            kstep_mma<!decltype(first)::value>(T, U, A[0], so[0]);
            WG_COMMIT();
#pragma unroll
            for (int i = 1; i < CH; i++) {
                if (rem == i) break;
                WG_FENCE();
                kstep_mma<true>(T, U, A[i], so[i]);
                WG_COMMIT();
            }
        };
        auto retire = [&]() {
            asm volatile("wgmma.wait_group.sync.aligned 0;"
                         : "+r"(A[0][0]), "+r"(A[0][1]), "+r"(A[0][2]), "+r"(A[0][3]), "+r"(A[1][0]), "+r"(A[1][1]),
                           "+r"(A[1][2]), "+r"(A[1][3]), "+r"(A[2][0]), "+r"(A[2][1]), "+r"(A[2][2]), "+r"(A[2][3]),
                           "+r"(A[3][0]), "+r"(A[3][1]), "+r"(A[3][2]), "+r"(A[3][3])::"memory");
            asm volatile("st.relaxed.cta.shared.u8 [%0], %1;" ::"r"(slot_addr + 8 + w), "r"(slot_lap + 1) : "memory");
        };
        uint2 ex = make_uint2(0u, 0u);
        auto fetch_u = [&]() {
            bar_named(wg + 2, 128);
            ex = lds64(ex_r + exo);
            exo ^= 1152;
        };
        auto store = [&](bool pred) {
            asm volatile("{.reg .pred p; setp.ne.u32 p, %2, 0; @p st.global.cs.u32 [%0], %1;}"
                         ::"l"(outp), "r"(pack_bf(o[0] + __uint_as_float(ex.x), o[2] + __uint_as_float(ex.y))), "r"((uint32_t)pred) : "memory");
        };
        auto tail = [&]() {
#pragma unroll
            for (int mt = 0; mt < 4; mt++) weigh(Y[mt], cy[mt], aY[mt]);
            o[0] = bf_lo(res);
            o[2] = bf_hi(res);
        };
        uint32_t rnext = lds32(sb + SM_KST + n * 4);
        t = rnext & 511;
        tend = (rnext >> 9) & 511;
        rnext = lds32(sb + SM_KST + (n + NCW) * 4);
#pragma unroll
        for (int i = 0; i < 32; i++) Y[i >> 3][i & 7] = 0.f;
#pragma unroll
        for (int i = 0; i < 16; i++) A[i >> 2][i & 3] = 0u;
        bool ready;
        locate();
        int lim = npg - MAXM;
        bool final = false;
        while (true) {
          if (n >= lim) {
              if (final) break;
              mbar_wait(bar_fin, 0);
              lim = lds32(sb + SM_FLAG + 8);
              final = true;
              continue;
          }
          wait_chunk();
          do {
            issue(TrueT());
            store(n >= 2 * NCW);
            tail();
            asm volatile("ld.global.L1::no_allocate.u32 %0, [%3];" : "=r"(res), "+f"(o[0]), "+f"(o[2]) : "l"(svp) : "memory");
            if (__builtin_expect(tend - t > CH, 0)) {
                do {
                    t += CH;
                    retire();
                    locate();
                    wait_chunk();
                    issue(FalseT());
                } while (tend - t > CH);
            }
            n += NCW;
            t = rnext & 511;
            tend = (rnext >> 9) & 511;
            outp += d2;
            d2 = d1;
            d1 = ((int)(rnext >> 18) - id0) * 128;
            id0 = rnext >> 18;
            svp += d1;
            retire();
            locate();
            ready = __all_sync(~0u, lane_ready()) && n < lim;
            prep_load();
            rnext = lds32(sb + SM_KST + (n + NCW) * 4);
            fetch_u();
            uint32_t tb[16], aU[3][2];
#pragma unroll
            for (int i = 0; i < 16; i++) tb[i] = pack_bf(T[2 * i], T[2 * i + 1]);
#pragma unroll
            for (int x = 0; x < 3; x++) weigh(U + 8 * x, cu, aU[x]);
#pragma unroll
            for (int i = 0; i < 32; i++) Y[i >> 3][i & 7] = 0.f;
            float u[4] = {0.f, 0.f, 0.f, 0.f};
#pragma unroll
            for (int kk = 0; kk < 4; kk++) {
                mma1688(o, aY[kk], one[kk]);
#pragma unroll
                for (int mt = 0; mt < 4; mt++) {
                    mma16816(Y[mt], wa[mt][kk], tb[4 * kk], tb[4 * kk + 2]);
                    mma16816(Y[mt] + 4, wa[mt][kk], tb[4 * kk + 1], tb[4 * kk + 3]);
                }
                if (kk < 3) mma1688(u, aU[kk], one[kk + 1]);
            }
            prep_mul();
            sts32f(ex_w + exo, u[0]);
            sts32f(ex_w + exo + 32, u[2]);
          } while (ready);
        }
        store(true);
        outp += d2;
        tail();
        fetch_u();
#pragma unroll
        for (int mt = 0; mt < 4; mt++) mma1688(o, aY[mt], one[mt]);
        store(true);
        STAMP(9);
        TWOUT(0, tw0);
    }
}

__global__ void bump_epoch_kernel() { g_epoch = (g_epoch + 1u) % TAGMAX; }

}

extern "C" void kernel_launch(void* const* d_in, const int* in_sizes, int n_in, void* d_out, int out_size) {
    const __nv_bfloat16* sv = (const __nv_bfloat16*)d_in[0];
    const __nv_bfloat16* pos = (const __nv_bfloat16*)d_in[1];
    const int* src = (const int*)d_in[2];
    const int* dst = (const int*)d_in[3];
    const __nv_bfloat16* freqs = (const __nv_bfloat16*)d_in[4];
    const __nv_bfloat16* w1 = (const __nv_bfloat16*)d_in[5];
    const __nv_bfloat16* w2 = (const __nv_bfloat16*)d_in[6];
    const __nv_bfloat16* wr = (const __nv_bfloat16*)d_in[7];
    __nv_bfloat16* out = (__nv_bfloat16*)d_out;
    static int fused = -1;
    if (fused < 0) {
        cudaFuncSetAttribute(painn_kernel<0>, cudaFuncAttributeMaxDynamicSharedMemorySize, SMEM_BYTES);
        cudaFuncSetAttribute(painn_kernel<1>, cudaFuncAttributeMaxDynamicSharedMemorySize, SMEM_BYTES);
        cudaFuncSetAttribute(painn_kernel<2>, cudaFuncAttributeMaxDynamicSharedMemorySize, SMEM_BYTES);
        int dev = 0, sms = 0, occ = 0;
        cudaGetDevice(&dev);
        cudaDeviceGetAttribute(&sms, cudaDevAttrMultiProcessorCount, dev);
        cudaOccupancyMaxActiveBlocksPerMultiprocessor(&occ, painn_kernel<0>, THREADS, SMEM_BYTES);
        fused = occ * sms >= G;
    }
    if (fused) {
        painn_kernel<0><<<G, THREADS, SMEM_BYTES>>>(sv, pos, src, dst, freqs, w1, w2, wr, out);
    } else {
        painn_kernel<1><<<G, THREADS, SMEM_BYTES>>>(sv, pos, src, dst, freqs, w1, w2, wr, out);
        painn_kernel<2><<<G, THREADS, SMEM_BYTES>>>(sv, pos, src, dst, freqs, w1, w2, wr, out);
        bump_epoch_kernel<<<1, 1>>>();
    }
}
```
